```python
import torch

def _softmax(x, axis=-1):
    return torch.softmax(x, dim=axis)

def _gelu(x):
    return torch.nn.functional.gelu(x, approximate='tanh')

def _silu(x):
    return torch.nn.functional.silu(x)

def _sigmoid(x):
    return torch.sigmoid(x)

def _layernorm(x, axis=-1, eps=1e-05):
    m = x.mean(dim=axis, keepdim=True)
    v = x.var(dim=axis, keepdim=True, unbiased=False)
    return (x - m) / torch.sqrt(v + eps)

def _scatter_add(tgt, idx, src, axis=0):
    return tgt.clone().index_add_(axis, idx, src)

def _segment_sum(src, seg, n):
    out = torch.zeros((n,) + src.shape[1:], dtype=src.dtype)
    return out.index_add_(0, seg, src)

def _pad(x, pw):
    flat = tuple((v for pair in reversed(pw) for v in pair))
    return torch.nn.functional.pad(x, flat)
kernel_name = 'adaLN_cond__compressed_kv_cla__swiglu_ffn__decode'

def setup_inputs():

    _w = lambda a: (lambda t: t.to(torch.bfloat16) if t.is_floating_point() else t)(torch.as_tensor(a))

    def _A_setup():
        B, H, Sq, Sk, D, M = (4, 32, 1, 4096, 128, 576)
        Dc = 4 * D
        return {'x': _w((lambda *s: torch.randn(*s, dtype=torch.bfloat16) * 0.05)(B, Sq, M)), 'c_kv': _w((lambda *s: torch.randn(*s, dtype=torch.bfloat16) * 1.6)(B, Sk, Dc)), 'w_q': _w((lambda *s: torch.randn(*s, dtype=torch.bfloat16) * 0.8)(M, H, D) * M ** (-0.5)), 'w_uk': _w((lambda *s: torch.randn(*s, dtype=torch.bfloat16) * 0.8)(Dc, H, D) * Dc ** (-0.5)), 'w_uv': _w((lambda *s: torch.randn(*s, dtype=torch.bfloat16) * 1.6)(Dc, H, D) * Dc ** (-0.5)), 'w_o': _w((lambda *s: torch.randn(*s, dtype=torch.bfloat16) * 1.6)(H, D, M) * (H * D) ** (-0.5))}
    _A_in = _A_setup()

    def _B_setup():
        B, S, D, F = (4, 1, 576, 4608)
        return {'x': _w((lambda *s: torch.randn(*s, dtype=torch.bfloat16) * 0.05)(B, S, D)), 'w_gate': _w((lambda *s: torch.randn(*s, dtype=torch.bfloat16) * 0.05)(D, F)), 'w_up': _w((lambda *s: torch.randn(*s, dtype=torch.bfloat16) * 0.05)(D, F)), 'w_down': _w((lambda *s: torch.randn(*s, dtype=torch.bfloat16) * 0.05)(F, D))}
    _B_in = _B_setup()
    return {'A_x': _A_in['x'], 'A_c_kv': _A_in['c_kv'], 'A_w_q': _A_in['w_q'], 'A_w_uk': _A_in['w_uk'], 'A_w_uv': _A_in['w_uv'], 'A_w_o': _A_in['w_o'], 'B_x': _B_in['x'], 'B_w_gate': _B_in['w_gate'], 'B_w_up': _B_in['w_up'], 'B_w_down': _B_in['w_down'], 'c': _w((lambda *s: torch.randn(*s, dtype=torch.bfloat16) * 0.1)(4, 576) * 8.0), 'w_mod': _w((lambda *s: torch.randn(*s, dtype=torch.bfloat16) * 0.1)(576, 6 * 576) * 576 ** (-0.5) * 8.0)}

def reference(A_x, A_c_kv, A_w_q, A_w_uk, A_w_uv, A_w_o, B_x, B_w_gate, B_w_up, B_w_down, c, w_mod):

    def _A_ref(x, c_kv, w_q, w_uk, w_uv, w_o):
        B, Sq, M = (x.shape[0], x.shape[1], x.shape[2])
        Sk = c_kv.shape[1]
        H, D = (w_q.shape[1], w_q.shape[2])
        q = torch.einsum('bqm,mhd->bhqd', x, w_q)
        k = torch.einsum('bkc,chd->bhkd', c_kv, w_uk)
        v = torch.einsum('bkc,chd->bhkd', c_kv, w_uv)
        scores = torch.einsum('bhqd,bhkd->bhqk', q, k) * D ** (-0.5)
        off = Sk - Sq
        qi = torch.arange(Sq)[:, None]
        kj = torch.arange(Sk)[None, :]
        cmask = kj <= qi + off
        scores = torch.where(cmask[None, None], scores, -1000000000.0)
        p = _softmax(scores, axis=-1)
        ctx = torch.einsum('bhqk,bhkd->bhqd', p, v)
        return torch.einsum('bhqd,hdm->bqm', ctx, w_o)

    def _B_ref(x, w_gate, w_up, w_down):
        g = _silu(x @ w_gate)
        u = x @ w_up
        return g * u @ w_down
    x = A_x
    mod = (_silu(c) @ w_mod).reshape(c.shape[0], 6, 1, -1)
    sa, ca, ga, sb, cb, gb = (mod[:, 0].clone(), mod[:, 1].clone(), mod[:, 2].clone(), mod[:, 3].clone(), mod[:, 4].clone(), mod[:, 5].clone())
    h = _layernorm(x, axis=-1) * (1 + ca) + sa
    x = x + ga * _A_ref(h, A_c_kv, A_w_q, A_w_uk, A_w_uv, A_w_o)
    h = _layernorm(x, axis=-1) * (1 + cb) + sb
    x = x + gb * _B_ref(h, B_w_gate, B_w_up, B_w_down)
    return x
```

```cpp
#include <cuda_runtime.h>
#include <cuda_bf16.h>
#include <cuda.h>
#include <stdint.h>

namespace {

constexpr int NCTA = 128;
constexpr int NTHR = 512;
constexpr int NRED = 72;
#define WIN 4
#define TSTART 450
#define RAMP 300

constexpr uint32_t OFF_CKV    = 0;
constexpr uint32_t OFF_RINGE  = 131072;
constexpr uint32_t OFF_WUV    = 0;
constexpr uint32_t OFF_MODR   = 32768;
constexpr uint32_t OFF_WUK    = 131072;
constexpr uint32_t OFF_SX     = OFF_WUK;
constexpr uint32_t OFF_INBOX3 = OFF_WUK;
constexpr uint32_t OFF_WQ     = 163840;
constexpr uint32_t OFF_SL     = OFF_WQ + 20480;
constexpr uint32_t OFF_MOD0   = 200704;
constexpr uint32_t OFF_STAT   = OFF_MOD0 + 16384;
constexpr uint32_t OFF_SP     = 219136;
constexpr uint32_t OFF_HS     = OFF_SP + 4544;
constexpr uint32_t OFF_X      = OFF_SP;
constexpr uint32_t OFF_C      = OFF_SP + 4608;
constexpr uint32_t OFF_CP     = OFF_SP;
constexpr uint32_t OFF_RED    = OFF_SP + 9216;
constexpr uint32_t OFF_BAR    = OFF_RED + 2560;
constexpr uint32_t OFF_LN1    = OFF_BAR + 672;
constexpr uint32_t OFF_XO     = OFF_LN1 + 32;
constexpr uint32_t OFF_SIDE   = OFF_XO + 64;
constexpr uint32_t OFF_TL     = OFF_SIDE + 32;
constexpr uint32_t SMEM_BYTES = OFF_TL + 256;
constexpr uint32_t OFF_LNST   = OFF_RED + 1024;
constexpr uint32_t OFF_ACT    = OFF_RED + 1536;
static_assert(SMEM_BYTES <= 232448, "smem");
static_assert(OFF_RED % 128 == 0 && OFF_HS % 16 == 0 && OFF_LN1 % 16 == 0, "align");

enum {
    B_WQ = 0, B_WUK = 4, B_CX = 8,
    B_CKV = 9,
    B_WUV = 25, B_SX = 29,
    B_CP = 37, B_QABS = 38, B_QP = 39, B_INB3 = 40,
    B_WO = 41, B_MOD = 45, B_WD = 49, B_GU = 55,
    B_PEER_WUK = 64, B_FREE_WQ = 65, B_FREE_QABS = 66, B_FREE_MOD = 67, B_FREE_T1 = 68, B_FREE_T4 = 69, B_FREE_RING = 70,
    B_FREE_WUV = 71, B_FREE_WO = 72, B_FREE_INB3 = 73, B_TAB = 74, B_PF = 75,
    B_COUNT = 83
};
__host__ __device__ constexpr uint32_t bar_count(int i) {
    return (i == B_QP || i == B_CP || i == B_FREE_WO) ? 9u : i == B_FREE_WQ ? 2u : i == B_FREE_WUV ? 8u
         : (i == B_FREE_T1 || i == B_FREE_T4 || i >= B_PF || i == B_FREE_RING) ? 4u : (i >= B_SX && i < B_CP) ? 5u : 1u;
}

constexpr int INB3_BYTES = 34816;

constexpr uint32_t PAGE = 2u << 20;
constexpr uint32_t G_EPOCH = 0, G_CNT = 8192, G_TAB = 16384, G_PROBE = 1900544;
constexpr uint32_t G_MODV = 65536;
constexpr uint32_t G_QABS = 196608;
constexpr uint32_t G_PART = 720896;
constexpr uint32_t G_STAT = 65536, G_INB = 131072;
__device__ uint4 g_scratch[6 * PAGE / 16];

__device__ __forceinline__ uint32_t dup(uint32_t l) { return ((l >> 12) << 13) | (l & 4095u); }
__device__ __forceinline__ uint32_t dup32(uint32_t l) { return ((l & 0x3000u) << 2) | ((l & 0x4000u) >> 1) | (l & 4095u); }
__device__ __forceinline__ uint32_t sided(uint32_t off, uint32_t side) { return off + (((__popc(off & 0xB2000u) ^ side) & 1u) << 12); }
__device__ __forceinline__ uint32_t modv_off(int rep, int col) { return G_MODV + rep * 65536 + dup(col * 8); }

#define TS(k)
#define TS0(k)
#define TSA(k)
#define TSD(k)
#define TSM(k)

struct Maps {
    CUtensorMap wq, wuk, wuv, ckv, wo, wd, mod, g32, u32, g48, u48, scr;
};

__device__ __forceinline__ void mbar_init(uint32_t bar, uint32_t cnt) {
    asm volatile("mbarrier.init.shared::cta.b64 [%0], %1;" ::"r"(bar), "r"(cnt) : "memory");
}
__device__ __forceinline__ void mbar_arrive_tx(uint32_t bar, uint32_t bytes) {
    asm volatile("mbarrier.arrive.expect_tx.shared::cta.b64 _, [%0], %1;" ::"r"(bar), "r"(bytes) : "memory");
}
__device__ __forceinline__ void mbar_arrive(uint32_t bar) {
    asm volatile("mbarrier.arrive.shared::cta.b64 _, [%0];" ::"r"(bar) : "memory");
}
__device__ __forceinline__ void mbar_arrive_remote(uint32_t cbar) {
    asm volatile("mbarrier.arrive.shared::cluster.b64 _, [%0];" ::"r"(cbar) : "memory");
}
__device__ __forceinline__ bool mbar_try(uint32_t bar, uint32_t parity) {
    uint32_t ok;
    asm volatile("{\n.reg .pred p;\nmbarrier.try_wait.parity.shared::cta.b64 p, [%1], %2;\nselp.u32 %0, 1, 0, p;\n}"
                 : "=r"(ok) : "r"(bar), "r"(parity) : "memory");
    return ok != 0;
}
__device__ __forceinline__ bool mbar_test(uint32_t bar, uint32_t parity) {
    uint32_t ok;
    asm volatile("{\n.reg .pred p;\nmbarrier.test_wait.parity.shared::cta.b64 p, [%1], %2;\nselp.u32 %0, 1, 0, p;\n}"
                 : "=r"(ok) : "r"(bar), "r"(parity) : "memory");
    return ok != 0;
}
__device__ __forceinline__ uint32_t mbar_wait_nt(uint32_t bar, uint32_t parity) {
    uint32_t left;
    asm volatile("{\n.reg .pred p, q;\n"
                 "mbarrier.try_wait.parity.shared::cta.b64 p, [%1], %2;\n"
                 "@p bra LAB_DONE;\n"
                 "mov.u32 %0, 0x100000;\n"
                 "LAB_WAIT:\n"
                 "mbarrier.try_wait.parity.shared::cta.b64 p, [%1], %2;\n"
                 "@p bra LAB_DONE;\n"
                 "sub.u32 %0, %0, 1;\n"
                 "setp.ne.u32 q, %0, 0;\n"
                 "@q bra LAB_WAIT;\n"
                 "LAB_DONE:\n"
                 "selp.u32 %0, 0, 1, p;\n}"
                 : "=r"(left) : "r"(bar), "r"(parity) : "memory");
    return left;
}
__device__ __noinline__ void mbar_wait_slow(uint32_t bar, uint32_t parity) {
    uint32_t n = 0;
    while (!mbar_try(bar, parity))
        if (++n > (1u << 20)) __trap();
}
__device__ __forceinline__ void mbar_wait(uint32_t bar, uint32_t parity) {
    if (!mbar_try(bar, parity)) mbar_wait_slow(bar, parity);
}
__device__ __forceinline__ void mbar_wait_n(uint32_t bar0, int n, int lane) {
    const uint32_t b = bar0 + 8u * (uint32_t)min(lane, n - 1);
    if (!__all_sync(~0u, mbar_try(b, 0))) {
        mbar_wait_slow(b, 0);
        __syncwarp();
    }
}
__device__ __forceinline__ void tma2d(uint32_t dst, const CUtensorMap* tm, int c0, int c1, uint32_t bar, uint64_t pol) {
    asm volatile("cp.async.bulk.tensor.2d.shared::cluster.global.mbarrier::complete_tx::bytes.L2::cache_hint [%0], [%1, {%3, %4}], [%2], %5;"
                 ::"r"(dst), "l"(tm), "r"(bar), "r"(c0), "r"(c1), "l"(pol) : "memory");
}
__device__ __forceinline__ void tma3d(uint32_t dst, const CUtensorMap* tm, int c1, int c2, uint32_t bar) {
    asm volatile("cp.async.bulk.tensor.3d.shared::cluster.global.mbarrier::complete_tx::bytes [%0], [%1, {%5, %3, %4}], [%2];"
                 ::"r"(dst), "l"(tm), "r"(bar), "r"(c1), "r"(c2), "r"(0) : "memory");
}
__device__ __forceinline__ void tma4d(uint32_t dst, const CUtensorMap* tm, int c0, int c2, int c3, uint32_t bar, uint64_t pol) {
    asm volatile("cp.async.bulk.tensor.4d.shared::cluster.global.mbarrier::complete_tx::bytes.L2::cache_hint [%0], [%1, {%3, %6, %4, %5}], [%2], %7;"
                 ::"r"(dst), "l"(tm), "r"(bar), "r"(c0), "r"(c2), "r"(c3), "r"(0), "l"(pol) : "memory");
}
__device__ __forceinline__ void bulk_g2s(uint32_t dst, const void* src, uint32_t bytes, uint32_t bar) {
    asm volatile("cp.async.bulk.shared::cluster.global.mbarrier::complete_tx::bytes [%0], [%1], %2, [%3];"
                 ::"r"(dst), "l"(src), "r"(bytes), "r"(bar) : "memory");
}
__device__ __forceinline__ void prefetch_map(const CUtensorMap* tm) {
    asm volatile("prefetch.tensormap [%0];" ::"l"(tm) : "memory");
}
__device__ __forceinline__ uint32_t mapa(uint32_t a, uint32_t rank) {
    uint32_t d;
    asm("mapa.shared::cluster.u32 %0, %1, %2;" : "=r"(d) : "r"(a), "r"(rank));
    return d;
}
__device__ __forceinline__ void st_async2(uint32_t caddr, float a, float b, uint32_t cbar) {
    asm volatile("st.async.shared::cluster.mbarrier::complete_tx::bytes.v2.f32 [%0], {%1, %2}, [%3];"
                 ::"r"(caddr), "f"(a), "f"(b), "r"(cbar) : "memory");
}
__device__ __forceinline__ void st_async4(uint32_t caddr, float a, float b, float c, float d, uint32_t cbar) {
    asm volatile("st.async.shared::cluster.mbarrier::complete_tx::bytes.v4.f32 [%0], {%1, %2, %3, %4}, [%5];"
                 ::"r"(caddr), "f"(a), "f"(b), "f"(c), "f"(d), "r"(cbar) : "memory");
}
__device__ __forceinline__ void ldsm4(uint32_t (&r)[4], uint32_t a) {
    asm volatile("ldmatrix.sync.aligned.m8n8.x4.shared.b16 {%0,%1,%2,%3}, [%4];"
                 : "=r"(r[0]), "=r"(r[1]), "=r"(r[2]), "=r"(r[3]) : "r"(a) : "memory");
}
__device__ __forceinline__ void ldsm4t(uint32_t (&r)[4], uint32_t a) {
    asm volatile("ldmatrix.sync.aligned.m8n8.x4.trans.shared.b16 {%0,%1,%2,%3}, [%4];"
                 : "=r"(r[0]), "=r"(r[1]), "=r"(r[2]), "=r"(r[3]) : "r"(a) : "memory");
}
__device__ __forceinline__ void mma(float (&d)[4], uint32_t a0, uint32_t a1, uint32_t a2, uint32_t a3, uint32_t b0, uint32_t b1) {
    asm("mma.sync.aligned.m16n8k16.row.col.f32.bf16.bf16.f32 {%0,%1,%2,%3}, {%4,%5,%6,%7}, {%8,%9}, {%0,%1,%2,%3};"
        : "+f"(d[0]), "+f"(d[1]), "+f"(d[2]), "+f"(d[3]) : "r"(a0), "r"(a1), "r"(a2), "r"(a3), "r"(b0), "r"(b1));
}
__device__ __forceinline__ void mma(float (&d)[4], const uint32_t (&a)[4], uint32_t b0, uint32_t b1) {
    mma(d, a[0], a[1], a[2], a[3], b0, b1);
}
__device__ __forceinline__ constexpr uint32_t desc_hi(uint32_t sbo, uint32_t swz) { return (sbo >> 4) | (swz << 30); }
__device__ __forceinline__ uint32_t desc_lo(uint32_t addr18, uint32_t lbo) { return (addr18 >> 4) | ((lbo >> 4) << 16); }
template <int ACC>
__device__ __forceinline__ void wgmma_s(float (&d)[32], uint32_t a, uint32_t b) {
    asm volatile("{\n.reg .b64 da, db;\nmov.b64 da, {%32, %34};\nmov.b64 db, {%33, %34};\n"
                 "wgmma.mma_async.sync.aligned.m64n64k16.f32.bf16.bf16 {%0,%1,%2,%3,%4,%5,%6,%7,%8,%9,%10,%11,%12,%13,%14,%15,%16,%17,%18,%19,%20,%21,%22,%23,%24,%25,%26,%27,%28,%29,%30,%31}, da, db, %35, 1, 1, 0, 0;\n}"
                 : "+f"(d[0]), "+f"(d[1]), "+f"(d[2]), "+f"(d[3]), "+f"(d[4]), "+f"(d[5]), "+f"(d[6]), "+f"(d[7]), "+f"(d[8]), "+f"(d[9]), "+f"(d[10]), "+f"(d[11]), "+f"(d[12]), "+f"(d[13]), "+f"(d[14]), "+f"(d[15]), "+f"(d[16]), "+f"(d[17]), "+f"(d[18]), "+f"(d[19]), "+f"(d[20]), "+f"(d[21]), "+f"(d[22]), "+f"(d[23]), "+f"(d[24]), "+f"(d[25]), "+f"(d[26]), "+f"(d[27]), "+f"(d[28]), "+f"(d[29]), "+f"(d[30]), "+f"(d[31])
                 : "r"(a), "r"(b), "r"(desc_hi(1024, 1)), "n"(ACC));
}
__device__ __forceinline__ void wgmma_pv(float (&d)[16], uint32_t a, uint32_t b) {
    asm volatile("{\n.reg .b64 da, db;\nmov.b64 da, {%16, %18};\nmov.b64 db, {%17, %19};\n"
                 "wgmma.mma_async.sync.aligned.m64n32k16.f32.bf16.bf16 {%0,%1,%2,%3,%4,%5,%6,%7,%8,%9,%10,%11,%12,%13,%14,%15}, da, db, 1, 1, 1, 1, 0;\n}"
                 : "+f"(d[0]), "+f"(d[1]), "+f"(d[2]), "+f"(d[3]), "+f"(d[4]), "+f"(d[5]), "+f"(d[6]), "+f"(d[7]), "+f"(d[8]), "+f"(d[9]), "+f"(d[10]), "+f"(d[11]), "+f"(d[12]), "+f"(d[13]), "+f"(d[14]), "+f"(d[15])
                 : "r"(a), "r"(b), "r"(desc_hi(2048, 1)), "r"(desc_hi(1024, 0)));
}
__device__ __forceinline__ void wg_fence() { asm volatile("wgmma.fence.sync.aligned;" ::: "memory"); }
__device__ __forceinline__ void wg_commit() { asm volatile("wgmma.commit_group.sync.aligned;" ::: "memory"); }
__device__ __forceinline__ void wg_wait0() { asm volatile("wgmma.wait_group.sync.aligned 0;" ::: "memory"); }
__device__ __forceinline__ void fence_async() { asm volatile("fence.proxy.async.shared::cta;" ::: "memory"); }
template <int N>
__device__ __forceinline__ void pin(float (&d)[N]) {
#pragma unroll
    for (int i = 0; i < N; i++) asm volatile("" : "+f"(d[i])::"memory");
}
__device__ __forceinline__ uint32_t pack2(float lo, float hi) {
    uint32_t d;
    asm("cvt.rn.bf16x2.f32 %0, %1, %2;" : "=r"(d) : "f"(hi), "f"(lo));
    return d;
}
__device__ __forceinline__ uint32_t pack2_tag(float lo, float hi, uint32_t par16) {
    uint32_t u = ((__float_as_uint(lo) + 0x10000u - par16) & 0xFFFE0000u) | par16;
    return __byte_perm(u, pack2(0.f, hi), 0x7632);
}
__device__ __forceinline__ float bf_lo(uint32_t w) { return __uint_as_float(w << 16); }
__device__ __forceinline__ float bf_hi(uint32_t w) { return __uint_as_float(w & 0xFFFF0000u); }
__device__ __forceinline__ float rcp(float x) {
    float y;
    asm("rcp.approx.ftz.f32 %0, %1;" : "=f"(y) : "f"(x));
    return y;
}
__device__ __forceinline__ float ex2(float x) {
    float y;
    asm("ex2.approx.ftz.f32 %0, %1;" : "=f"(y) : "f"(x));
    return y;
}
__device__ __forceinline__ float silu(float x) { return x * rcp(1.f + ex2(-1.4426950408889634f * x)); }
__device__ __forceinline__ uint32_t clock_after(uint32_t dep) {
    uint32_t c;
    asm volatile("{\n.reg .pred p;\nsetp.eq.u32 p, %1, 0;\nmov.u32 %0, 0;\n@p mov.u32 %0, %clock;\n}" : "=r"(c) : "r"(dep) : "memory");
    return c;
}
__device__ __forceinline__ uint32_t gtime() {
    uint32_t t;
    asm volatile("mov.u32 %0, %globaltimer_lo;" : "=r"(t));
    return t;
}
__device__ __forceinline__ uint32_t ldg_v(const void* p) {
    uint32_t v;
    asm volatile("ld.global.nc.u32 %0, [%1];" : "=r"(v) : "l"(p) : "memory");
    return v;
}
__device__ __forceinline__ uint32_t ldg_v16(const void* p) {
    uint32_t v;
    asm volatile("ld.global.nc.u16 %0, [%1];" : "=r"(v) : "l"(p) : "memory");
    return v;
}
__device__ __forceinline__ uint4 ld_poll4(const void* p) {
    uint64_t lo, hi;
    asm volatile("ld.relaxed.gpu.global.v2.b64 {%0,%1}, [%2];" : "=l"(lo), "=l"(hi) : "l"(p) : "memory");
    return make_uint4((uint32_t)lo, (uint32_t)(lo >> 32), (uint32_t)hi, (uint32_t)(hi >> 32));
}
__device__ __forceinline__ uint2 ld_poll2(const void* p) {
    uint64_t v;
    asm volatile("ld.relaxed.gpu.global.b64 %0, [%1];" : "=l"(v) : "l"(p) : "memory");
    return make_uint2((uint32_t)v, (uint32_t)(v >> 32));
}
__device__ __forceinline__ void st_pub2(void* p, uint32_t a, uint32_t b) {
    asm volatile("st.relaxed.gpu.global.b64 [%0], %1;" ::"l"(p), "l"((uint64_t)a | ((uint64_t)b << 32)) : "memory");
}
__device__ __forceinline__ uint32_t ld_poll(const void* p) {
    uint32_t v;
    asm volatile("ld.relaxed.gpu.global.u32 %0, [%1];" : "=r"(v) : "l"(p) : "memory");
    return v;
}
__device__ __forceinline__ void st_pub(void* p, uint32_t v) {
    asm volatile("st.relaxed.gpu.global.u32 [%0], %1;" ::"l"(p), "r"(v) : "memory");
}
__device__ __forceinline__ void st_pub4(void* p, uint32_t a, uint32_t b, uint32_t c, uint32_t d) {
    uint64_t lo = (uint64_t)a | ((uint64_t)b << 32), hi = (uint64_t)c | ((uint64_t)d << 32);
    asm volatile("st.relaxed.gpu.global.v2.b64 [%0], {%1, %2};" ::"l"(p), "l"(lo), "l"(hi) : "memory");
}
__device__ __forceinline__ void red_add(void* p, uint32_t v) {
    asm volatile("red.relaxed.gpu.global.add.u32 [%0], %1;" ::"l"(p), "r"(v) : "memory");
}
__device__ __forceinline__ uint32_t lds32(uint32_t a) {
    uint32_t v;
    asm volatile("ld.shared.u32 %0, [%1];" : "=r"(v) : "r"(a) : "memory");
    return v;
}
__device__ __forceinline__ uint32_t lds16(uint32_t a) {
    uint32_t v;
    asm volatile("ld.shared.u16 %0, [%1];" : "=r"(v) : "r"(a) : "memory");
    return v;
}
__device__ __forceinline__ float ldsf(uint32_t a) { return __uint_as_float(lds32(a)); }
__device__ __forceinline__ float2 lds64f(uint32_t a) {
    float2 v;
    asm volatile("ld.shared.v2.f32 {%0,%1}, [%2];" : "=f"(v.x), "=f"(v.y) : "r"(a) : "memory");
    return v;
}
__device__ __forceinline__ void sts32(uint32_t a, uint32_t v) { asm volatile("st.shared.u32 [%0], %1;" ::"r"(a), "r"(v) : "memory"); }
__device__ __forceinline__ void stsf(uint32_t a, float v) { sts32(a, __float_as_uint(v)); }
__device__ __forceinline__ void sts16(uint32_t a, uint32_t v) { asm volatile("st.shared.u16 [%0], %1;" ::"r"(a), "h"((uint16_t)v) : "memory"); }
__device__ __forceinline__ void sts64(uint32_t a, uint32_t x, uint32_t y) {
    asm volatile("st.shared.v2.u32 [%0], {%1,%2};" ::"r"(a), "r"(x), "r"(y) : "memory");
}
__device__ __forceinline__ void sts64f(uint32_t a, float x, float y) { sts64(a, __float_as_uint(x), __float_as_uint(y)); }
__device__ __forceinline__ void bar_all() { asm volatile("bar.sync 1, 288;" ::: "memory"); }
__device__ __forceinline__ void bar_sync(int id, int n) { asm volatile("bar.sync %0, %1;" ::"r"(id), "r"(n) : "memory"); }
__device__ __forceinline__ void bar_arrive(int id, int n) { asm volatile("bar.arrive %0, %1;" ::"r"(id), "r"(n) : "memory"); }
__device__ __forceinline__ uint4 lds128(uint32_t a) {
    uint4 v;
    asm volatile("ld.shared.v4.u32 {%0,%1,%2,%3}, [%4];" : "=r"(v.x), "=r"(v.y), "=r"(v.z), "=r"(v.w) : "r"(a) : "memory");
    return v;
}
__device__ __forceinline__ float4 lds128f(uint32_t a) {
    float4 v;
    asm volatile("ld.shared.v4.f32 {%0,%1,%2,%3}, [%4];" : "=f"(v.x), "=f"(v.y), "=f"(v.z), "=f"(v.w) : "r"(a) : "memory");
    return v;
}
__device__ __forceinline__ void sts128(uint32_t a, uint32_t x, uint32_t y, uint32_t z, uint32_t w) {
    asm volatile("st.shared.v4.u32 [%0], {%1,%2,%3,%4};" ::"r"(a), "r"(x), "r"(y), "r"(z), "r"(w) : "memory");
}
__device__ __forceinline__ void sts128f(uint32_t a, float x, float y, float z, float w) {
    sts128(a, __float_as_uint(x), __float_as_uint(y), __float_as_uint(z), __float_as_uint(w));
}
__device__ __forceinline__ uint32_t hadd2(uint32_t a, uint32_t b) {
    __nv_bfloat162 s = __hadd2(*(__nv_bfloat162*)&a, *(__nv_bfloat162*)&b);
    return *(uint32_t*)&s;
}
__device__ __forceinline__ bool bar8_or(bool p) {
    uint32_t r;
    asm volatile("{\n.reg .pred q, o;\nsetp.ne.u32 q, %1, 0;\nbar.red.or.pred o, 3, 256, q;\nselp.u32 %0, 1, 0, o;\n}"
                 : "=r"(r) : "r"((uint32_t)p) : "memory");
    return r != 0;
}
__device__ __forceinline__ bool bar_and(int id, int n, bool p) {
    uint32_t r;
    asm volatile("{\n.reg .pred q, o;\nsetp.ne.u32 q, %1, 0;\nbar.red.and.pred o, %2, %3, q;\nselp.u32 %0, 1, 0, o;\n}"
                 : "=r"(r) : "r"((uint32_t)p), "r"(id), "r"(n) : "memory");
    return r != 0;
}
template <int V> struct IC { static constexpr int value = V; };
__device__ __forceinline__ float shfl_xor_v(float v, int m) {
    float r;
    asm volatile("shfl.sync.bfly.b32 %0, %1, %2, 0x1f, 0xffffffff;" : "=f"(r) : "f"(v), "r"(m));
    return r;
}
#define SPIN_GUARD(n) do { if (++(n) > (1u << 20)) __trap(); } while (0)

__device__ __forceinline__ float4 reduce_partials(const char* gb, int j, uint32_t side, uint32_t tagbit, uint32_t sb, int tid, int w, int lane, int tsb) {
    if (w < 8) {
        const char* p0 = gb + sided(G_PART + j * 16384 + tid * 16, side);
        const char* p1 = gb + sided(G_PART + j * 16384 + 8192 + tid * 16, side);
        uint4 v0, v1;
        uint32_t n = 0;
        while (true) {
            v0 = ld_poll4(p0);
            v1 = ld_poll4(p1);
            const uint32_t a = v0.x & v0.y & v0.z & v0.w & v1.x & v1.y & v1.z & v1.w;
            const uint32_t o = v0.x | v0.y | v0.z | v0.w | v1.x | v1.y | v1.z | v1.w;
            if (__all_sync(~0u, ((tagbit ? a : ~o) & 1u) != 0)) break;
            SPIN_GUARD(n);
        }
        TSM(tsb);
        float s[8];
        s[0] = bf_lo(v0.x) + bf_lo(v1.x); s[1] = bf_hi(v0.x) + bf_hi(v1.x);
        s[2] = bf_lo(v0.y) + bf_lo(v1.y); s[3] = bf_hi(v0.y) + bf_hi(v1.y);
        s[4] = bf_lo(v0.z) + bf_lo(v1.z); s[5] = bf_hi(v0.z) + bf_hi(v1.z);
        s[6] = bf_lo(v0.w) + bf_lo(v1.w); s[7] = bf_hi(v0.w) + bf_hi(v1.w);
        const bool u4 = lane & 16, u3 = lane & 8, u2 = lane & 4;
#pragma unroll
        for (int i = 0; i < 4; i++) {
            const float keep = u4 ? s[i + 4] : s[i], send = u4 ? s[i] : s[i + 4];
            s[i] = keep + __shfl_xor_sync(~0u, send, 16);
        }
#pragma unroll
        for (int i = 0; i < 2; i++) {
            const float keep = u3 ? s[i + 2] : s[i], send = u3 ? s[i] : s[i + 2];
            s[i] = keep + __shfl_xor_sync(~0u, send, 8);
        }
        {
            const float keep = u2 ? s[1] : s[0], send = u2 ? s[0] : s[1];
            s[0] = keep + __shfl_xor_sync(~0u, send, 4);
        }
        stsf(sb + OFF_RED + (w * 32 + (lane & 3) * 8 + (lane >> 2)) * 4, s[0]);
        if (w != 0) bar_arrive(2, 256);
    }
    float4 t = make_float4(0.f, 0.f, 0.f, 0.f);
    if (w == 0) {
        bar_sync(2, 256);
        float4 v[8];
#pragma unroll
        for (int i = 0; i < 8; i++) v[i] = lds128f(sb + OFF_RED + i * 128 + (lane & 7) * 16);
        t.x = ((v[0].x + v[1].x) + (v[2].x + v[3].x)) + ((v[4].x + v[5].x) + (v[6].x + v[7].x));
        t.y = ((v[0].y + v[1].y) + (v[2].y + v[3].y)) + ((v[4].y + v[5].y) + (v[6].y + v[7].y));
        t.z = ((v[0].z + v[1].z) + (v[2].z + v[3].z)) + ((v[4].z + v[5].z) + (v[6].z + v[7].z));
        t.w = ((v[0].w + v[1].w) + (v[2].w + v[3].w)) + ((v[4].w + v[5].w) + (v[6].w + v[7].w));
    }
    return t;
}

__device__ __forceinline__ void load_wide_frags(uint32_t (&a)[4][4], uint32_t base, int s, int w, int lane) {
    const int i = lane >> 3, rho = lane & 7;
    const int seg = (16 * s + (i >> 1) * 8 + rho) * 9 + w;
#pragma unroll
    for (int mt = 0; mt < 4; mt++) ldsm4t(a[mt], base + seg * 128 + (((2 * mt + (i & 1)) ^ (seg & 7)) << 4));
}

__device__ __forceinline__ void partial_slots(uint32_t (&po)[4], uint32_t sb, int id, int w, int lane) {
    const uint32_t km = lds32(sb + OFF_SIDE + 16 + (w >> 2) * 4) >> ((w & 3) * 8 + ((lane >> 1) & 1));
#pragma unroll
    for (int mt = 0; mt < 4; mt++)
        po[mt] = sided(G_PART + (8 * w + 2 * mt + ((lane >> 1) & 1)) * 16384 + dup(id * 64), km >> (2 * mt)) + (lane >> 2) * 8 + (lane & 1) * 4;
}
__device__ __forceinline__ void send_partials(char* gb, const uint32_t (&po)[4], const float (&d)[4][4], int lane, uint32_t tag16) {
    const bool hi = lane & 2;
#pragma unroll
    for (int mt = 0; mt < 4; mt++) st_pub(gb + po[mt], pack2_tag(hi ? d[mt][2] : d[mt][0], hi ? d[mt][3] : d[mt][1], tag16));
}

__global__ void __launch_bounds__(NTHR, 1) __cluster_dims__(2, 1, 1)
fused_kernel(const __nv_bfloat16* __restrict__ x, const __nv_bfloat16* __restrict__ cvec, const __nv_bfloat16* __restrict__ w_mod,
             __nv_bfloat16* __restrict__ out, char* __restrict__ gb, const __grid_constant__ Maps maps) {
    extern __shared__ __align__(1024) unsigned char smem[];
    const uint32_t sb = (uint32_t)__cvta_generic_to_shared(smem);
    const int tid = threadIdx.x, w = __shfl_sync(~0u, tid >> 5, 0), lane = tid & 31;
    const int id = blockIdx.x, P = id >> 1, r = id & 1;
    const int h = P >> 1, p = P & 1;
    const bool heavy = (P & 3) == 3;
    const int lp = (P >> 2) * 3 + (P & 3);
    const bool is_red = !heavy && (lp & 3) != 3;
    const int j = ((lp >> 2) * 3 + (lp & 3)) * 2 + r;
    const int f0 = heavy ? 3072 + 48 * ((P >> 2) * 2 + r) : 32 * (lp * 2 + r);
    const uint32_t gubox = heavy ? 6144u : 4096u;
    const uint32_t wdbase = heavy ? OFF_WQ - 18432 : OFF_WQ;
    const int g = lane >> 2, t = lane & 3;
    const int i4 = lane >> 3, rho = lane & 7;
    auto BAR = [&](int i) { return sb + OFF_BAR + 8u * i; };
    TS0(0);

    auto init_bars = [&](auto Q) {
        constexpr int lo = B_CKV + 15 * decltype(Q)::value, hi = lo + 15 < B_COUNT ? lo + 15 : B_COUNT;
        bar_sync(12, 192);
        if (lane == 0) {
#pragma unroll
            for (int i = lo; i < hi; i++) mbar_init(BAR(i), bar_count(i));
            asm volatile("fence.mbarrier_init.release.cluster;" ::: "memory");
        }
        __syncwarp();
        const int i = lo + lane;
        if (lane < 15 && i < B_PEER_WUK)
            mbar_arrive_tx(BAR(i), i < B_SX + 6 ? 8192u : i <= B_CP ? 4096u : i == B_QABS ? 32768u : i == B_QP ? 2048u
                                 : i == B_INB3 ? (uint32_t)INB3_BYTES : i < B_GU ? 9216u : 2 * gubox);
        __syncwarp();
        bar_arrive(9, 192);
        bar_arrive(13, 192);
        constexpr int b = decltype(Q)::value;
        if (b != 4) {
            mbar_wait(BAR(B_CX), 0);
            float xv[18];
#pragma unroll
            for (int i = 0; i < 9; i++) {
                const uint32_t v = lds32(sb + OFF_X + b * 1152 + i * 128 + lane * 4);
                xv[2 * i] = bf_lo(v);
                xv[2 * i + 1] = bf_hi(v);
            }
            float s = 0.f;
#pragma unroll
            for (int i = 0; i < 18; i++) s += xv[i];
#pragma unroll
            for (int o = 16; o; o >>= 1) s += __shfl_xor_sync(~0u, s, o);
            const float mean = s * (1.f / 576.f);
            float q2 = 0.f;
#pragma unroll
            for (int i = 0; i < 18; i++) q2 += (xv[i] - mean) * (xv[i] - mean);
#pragma unroll
            for (int o = 16; o; o >>= 1) q2 += __shfl_xor_sync(~0u, q2, o);
            if (lane == 0) {
                stsf(sb + OFF_LN1 + b * 4, mean);
                stsf(sb + OFF_LN1 + 16 + b * 4, rsqrtf(q2 * (1.f / 576.f) + 1e-5f));
            }
            __syncwarp();
        }
        asm volatile("barrier.cluster.arrive.relaxed.aligned;" ::: "memory");
    };

    auto fetch32 = [&](uint32_t dst, uint32_t off, uint32_t sd, uint32_t bar) {
        const uint32_t o0 = sided(off, sd), o1 = sided(off + 8192, sd);
        tma3d(dst, &maps.scr, (o0 >> 11) & 7, o0 >> 14, bar);
        tma3d(dst + 16384, &maps.scr, (o1 >> 11) & 7, o1 >> 14, bar);
    };
    auto fetch_qabs = [&]() {
        if (lane == 0) fetch32(sb + OFF_WQ, G_QABS + ((P >> 4) * 2 + r) * 65536, lds32(sb + OFF_SIDE), BAR(B_QABS));
        __syncwarp();
    };
    auto fetch_inbox = [&]() {
        const uint32_t pg = (1 + (id >> 5)) * PAGE, ib = (h * 2 + r) & 15, sd = lds32(sb + OFF_SIDE + 4);
        if (lane == 0) {
            fetch32(sb + OFF_INBOX3, pg + G_INB + ib * 65536, sd, BAR(B_INB3));
            bulk_g2s(sb + OFF_STAT, gb + sided(pg + G_STAT + dup(ib * 2048), sd), 2048, BAR(B_INB3));
        }
        __syncwarp();
    };

    if (w == 13) {
        if (lane == 0) {
            mbar_init(BAR(B_CX), 1);
            mbar_arrive_tx(BAR(B_CX), 9216);
            bulk_g2s(sb + OFF_C, cvec, 4608, BAR(B_CX));
            bulk_g2s(sb + OFF_X, x, 4608, BAR(B_CX));
        }
        __syncwarp();
        bar_arrive(14, 320);
        init_bars(IC<3>());
        bar_sync(4, NTHR);
        if (lane == 0) prefetch_map(&maps.scr);
        const uint32_t target = lds32(sb + OFF_SIDE + 28) * 64u;
        const char* cnt = gb + sided(G_CNT + (r * 4 + (P & 3)) * 128, lds32(sb + OFF_SIDE));
        uint32_t n = 0;
        while (ld_poll(cnt) != target) SPIN_GUARD(n);
        TS(10);
        mbar_wait(BAR(B_FREE_WQ), 0);
        fetch_qabs();
        TS(45);
        mbar_wait(BAR(B_TAB), 0);
        mbar_wait(BAR(B_FREE_RING), 0);
        if (lane == 0) prefetch_map(&maps.scr);
        n = 0;
        while (ld_poll(cnt + 1024) != target) SPIN_GUARD(n);
        TS(15);
        fetch_inbox();
        return;
    }
    if (w == 14) {
        init_bars(IC<4>());
        bar_sync(4, NTHR);
        uint32_t cw[72];
        if (is_red) {
#pragma unroll
            for (int s = 0; s < 18; s++) {
                const uint4 v = lds128(sb + OFF_MOD0 + (s >> 1) * 2048 + (s & 1) * 256 + (lane & 15) * 16);
                cw[4 * s] = v.x; cw[4 * s + 1] = v.y; cw[4 * s + 2] = v.z; cw[4 * s + 3] = v.w;
            }
        }
        __syncwarp();
        if (lane == 0) mbar_arrive(BAR(B_FREE_WQ));
        if (is_red) {
            const uint32_t par16 = (lds32(sb + OFF_SIDE + 28) & 1u) << 16;
            float d[2][2][4];
#pragma unroll
            for (int a = 0; a < 4; a++) d[a >> 1][a & 1][0] = d[a >> 1][a & 1][1] = d[a >> 1][a & 1][2] = d[a >> 1][a & 1][3] = 0.f;
#pragma unroll
            for (int bx = 0; bx < 4; bx++) {
                mbar_wait(BAR(B_MOD + bx), 0);
                const uint32_t mb = sb + OFF_MODR + bx * 9216 + ((i4 >> 1) * 8 + rho) * 64;
#pragma unroll
                for (int s = 0; s < 9; s++)
#pragma unroll
                    for (int mt = 0; mt < 2; mt++) {
                        uint32_t a[4];
                        ldsm4t(a, mb + s * 1024 + (((2 * mt + (i4 & 1)) ^ (rho >> 1)) << 4));
                        mma(d[mt][s & 1], a, cw[18 * bx + 2 * s], cw[18 * bx + 2 * s + 1]);
                    }
            }
            __syncwarp();
            if (lane == 0) mbar_arrive(BAR(B_FREE_MOD));
#pragma unroll
            for (int mt = 0; mt < 2; mt++) {
                const float v0 = t < 2 ? d[mt][0][0] + d[mt][1][0] : d[mt][0][2] + d[mt][1][2];
                const float v1 = t < 2 ? d[mt][0][1] + d[mt][1][1] : d[mt][0][3] + d[mt][1][3];
                const uint32_t mine = (t & 1) ? pack2(v0, v1) : pack2_tag(v0, v1, par16);
                const uint32_t other = __shfl_xor_sync(~0u, mine, 1);
                const int col = 1152 + 32 * j + 16 * mt + 8 * (t >> 1) + g;
                const uint32_t lo = (t & 1) ? other : mine, hi = (t & 1) ? mine : other;
                st_pub2(gb + modv_off(t & 1, col), lo, hi);
                st_pub2(gb + modv_off(t & 1, col) + 4096, lo, hi);
            }
            if (lane == 0) TS(34);
        }
        return;
    }
    if (w == 15) {
        asm volatile("barrier.cluster.arrive.relaxed.aligned;" ::: "memory");
        const uint32_t off0 = G_PROBE + dup(id * 256), off1 = (1 + (id >> 5)) * PAGE + dup((id & 31) * 256);
        st_pub4(gb + off0 + (lane >> 4) * 4096 + (lane & 15) * 16, 0, 0, 0, 0);
        st_pub4(gb + off1 + (lane >> 4) * 4096 + (lane & 15) * 16, 0, 0, 0, 0);
        const uint32_t ep = ld_poll(gb + G_EPOCH) + 1;
        auto probe = [&](uint32_t off, uint32_t dep) {
            uint32_t best0 = ~0u, best1 = ~0u;
#pragma unroll
            for (int i = 0; i < 4; i++) {
                const uint32_t c0 = clock_after(dep);
                dep = ld_poll(gb + off + (i & 1) * 4096 + (i >> 1) * 128 + dep);
                const uint32_t dt = clock_after(dep) - c0;
                if (i & 1) best1 = min(best1, dt);
                else best0 = min(best0, dt);
            }
            return __shfl_sync(~0u, (__popc(off & 0xB2000u) ^ (best1 < best0 ? 1u : 0u)) & 1u, 0);
        };
        const uint32_t s0 = probe(off0, ep == 0xFFFFFFFFu ? 4u : 0u);
        if (lane == 0) { sts32(sb + OFF_SIDE, s0); sts32(sb + OFF_SIDE + 28, ep); }
        TS(37);
        __syncwarp();
        bar_arrive(4, NTHR);
        const uint32_t s1 = probe(off1, 0u);
        const uint32_t word = ep * 4 + s1 * 2 + s0;
        if (lane < 2) st_pub(gb + G_TAB + lane * 4096 + id * 4, word);
        else if (lane < 4 && is_red) st_pub(gb + G_TAB + (lane & 1) * 4096 + 512 + j * 4, word);
        const char* tab = gb + sided(G_TAB, s0);
        uint4 hv;
        uint32_t r0, r1, r2, n = 0;
        while (true) {
            __nanosleep(200);
            hv = ld_poll4(tab + lane * 16);
            r0 = ld_poll(tab + 512 + lane * 4);
            r1 = ld_poll(tab + 640 + lane * 4);
            r2 = lane < 8 ? ld_poll(tab + 768 + lane * 4) : word;
            const uint32_t bad = (hv.x ^ word) | (hv.y ^ word) | (hv.z ^ word) | (hv.w ^ word) | (r0 ^ word) | (r1 ^ word) | (r2 ^ word);
            if (__all_sync(~0u, bad < 4u)) break;
            SPIN_GUARD(n);
        }
        const uint32_t ma = __ballot_sync(~0u, (r ? hv.y : hv.x) & 2u), mb = __ballot_sync(~0u, (r ? hv.w : hv.z) & 2u);
        const uint32_t k0 = __ballot_sync(~0u, r0 & 1u), k1 = __ballot_sync(~0u, r1 & 1u), k2 = __ballot_sync(~0u, r2 & 1u);
        bar_sync(13, 192);
        if (lane == 0) {
            sts32(sb + OFF_SIDE + 4, s1);
            sts64(sb + OFF_SIDE + 8, ma, mb);
            sts128(sb + OFF_SIDE + 16, k0, k1, k2, ep);
        }
#pragma unroll 1
        for (int i = 0; i < 9; i++) {
            const int jj = i * 8 + g;
            const uint32_t km = i < 4 ? k0 : i < 8 ? k1 : k2;
            st_pub4(gb + sided(G_PART + jj * 16384 + dup(id * 64), km >> (jj & 31)) + t * 16, 0, 0, 0, 0);
        }
        if (is_red) st_pub2(gb + modv_off(lane >> 4, 6 * 576 + 8 * j + rho) + (i4 & 1) * 4096, (ep & 1u) ^ 1u, 0u);
        __syncwarp();
        if (lane == 0) mbar_arrive(BAR(B_TAB));
        TS(38);
        return;
    }
    if (w == 12) {
        uint64_t pol;
        asm volatile("createpolicy.fractional.L2::evict_first.b64 %0, 1.0;" : "=l"(pol));
        const uint32_t t0 = gtime();
        if (lane == 0) {
            prefetch_map(&maps.wq);
#pragma unroll
            for (int i = 0; i < 8; i++) mbar_init(BAR(B_WQ + i), 1);
        }
        __syncwarp();
        if (lane < 8) mbar_arrive_tx(BAR(B_WQ + lane), lane < 4 ? 9216u : 8192u);
        __syncwarp();
        bar_arrive(12, 192);
        asm volatile("barrier.cluster.arrive.relaxed.aligned;" ::: "memory");
        bar_arrive(4, NTHR);
        uint32_t q[WIN];
#pragma unroll
        for (int i = 0; i < WIN; i++) q[i] = BAR(B_WUK + 3) | 1u;
        auto pace = [&](uint32_t nb) {
            mbar_wait(q[0] & ~1u, q[0] & 1u);
#pragma unroll
            for (int i = 0; i + 1 < WIN; i++) q[i] = q[i + 1];
            q[WIN - 1] = nb;
        };
        const bool l0 = lane == 0;
        const CUtensorMap* mg = heavy ? &maps.g48 : &maps.g32;
#pragma unroll 1
        for (int i = 0; i < 4; i++) {
            pace(BAR(B_WQ + i));
            while (gtime() - t0 < (uint32_t)(TSTART + i * RAMP));
            if (l0) {
                tma2d(sb + OFF_WQ + i * 9216, &maps.wq, 128 * h + 64 * p, 288 * r + 72 * i, BAR(B_WQ + i), pol);
                if (i == 0) { TS(29); prefetch_map(&maps.wuk); prefetch_map(&maps.ckv); }
            }
        }
#pragma unroll 1
        for (int i = 0; i < 4; i++) {
            pace(BAR(B_WUK + i));
            while (gtime() - t0 < (uint32_t)(TSTART + (4 + i) * RAMP));
            if (l0) tma2d(sb + OFF_WUK + i * 8192, &maps.wuk, 128 * h + 64 * p, 256 * r + 64 * i, BAR(B_WUK + i), pol);
        }
        __syncwarp();
        bar_sync(9, 192);
#pragma unroll 1
        for (int i = 0; i < 16; i++) {
            pace(BAR(B_CKV + i));
            if (l0) {
                tma4d(sb + OFF_CKV + i * 8192, &maps.ckv, 64 * (i & 1), 2 * r, 32 * P + 4 * (i >> 1), BAR(B_CKV + i), pol);
                if (i >= 2 && i < 8) prefetch_map(i == 2 ? &maps.mod : i == 3 ? &maps.wuv : i == 4 ? &maps.wo : i == 5 ? mg : i == 6 ? mg + 1 : &maps.wd);
            }
        }
        TS(30);
        mbar_wait(BAR(B_FREE_T1), 0);
#pragma unroll 1
        for (int i = 0; i < 4; i++) {
            pace(BAR(B_WUV + i));
            if (l0) tma2d(sb + OFF_WUV + i * 8192, &maps.wuv, 128 * h + 64 * p, 256 * r + 64 * i, BAR(B_WUV + i), pol);
        }
        TS(44);
        if (is_red) {
            mbar_wait(BAR(B_FREE_T4), 0);
#pragma unroll 1
            for (int k = 0; k < 4; k++) {
                pace(BAR(B_MOD + k));
                if (l0) tma2d(sb + OFF_MODR + k * 9216, &maps.mod, 1152 + 32 * j, 144 * k, BAR(B_MOD + k), pol);
            }
        }
#pragma unroll 1
        for (int i = 0; i < 4; i++) {
            if (i == 2) mbar_wait(BAR(B_FREE_RING), 0);
            pace(BAR(B_WO + i));
            if (l0) tma2d(sb + OFF_WQ + i * 9216, &maps.wo, 0, (32 * id + 8 * i) * 9, BAR(B_WO + i), pol);
        }
        TS(31);
#pragma unroll 1
        for (int i = 0; i < 9; i++) {
            if (is_red && i == 7) mbar_wait(BAR(B_FREE_MOD), 0);
            if (heavy && i == 8) mbar_wait(BAR(B_FREE_WUV), 0);
            pace(BAR(B_GU + i));
            const uint32_t dst = sb + OFF_RINGE - (i + 1) * 2 * gubox;
            if (l0) {
                tma2d(dst, mg, f0, 64 * i, BAR(B_GU + i), pol);
                tma2d(dst + gubox, mg + 1, f0, 64 * i, BAR(B_GU + i), pol);
            }
        }
        TS(32);
        mbar_wait(BAR(B_FREE_WO), 0);
        mbar_wait(BAR(B_FREE_INB3), 0);
        const int nwd = heavy ? 6 : 4;
#pragma unroll 1
        for (int i = 0; i < nwd; i++) {
            if (!(heavy && i < 2)) pace(BAR(B_WD + i));
            if (l0) tma2d(sb + wdbase + i * 9216, &maps.wd, 0, (f0 + 8 * i) * 9, BAR(B_WD + i), pol);
        }
        TS(33);
        return;
    }

    const uint32_t peer = r ^ 1;
    const int rep = P & 1;

    if (is_red && w < 9) {
        const char* wm = (const char*)w_mod + (size_t)(64 * w + (lane >> 1)) * 6912 + j * 32 + (lane & 1) * 16;
        const uint32_t d0 = sb + OFF_MOD0 + (64 * w + (lane >> 1)) * 32 + (((lane ^ (lane >> 3)) & 1) << 4);
#pragma unroll
        for (int q = 0; q < 4; q++)
            asm volatile("cp.async.cg.shared.global.L2::128B [%0], [%1], 16;" ::"r"(d0 + q * 512), "l"(wm + q * 16 * 6912) : "memory");
    }
    __syncwarp();
    if (w == 9) init_bars(IC<0>());
    if (w == 10) init_bars(IC<1>());
    if (w == 11) init_bars(IC<2>());
    auto parity = [&]() { return lds32(sb + OFF_SIDE + 28) & 1u; };
    if (w >= 9) bar_sync(4, NTHR);
    if (w < 9) {
    uint32_t ep_raw = 0;
    if (is_red && w < 2) ep_raw = ld_poll(gb + G_EPOCH);
    uint2 sav, cav;
    if (!is_red) {
        sav = ld_poll2(gb + modv_off((P >> 2) & 1, 288 * r + tid) + ((P >> 3) & 1) * 4096);
        cav = ld_poll2(gb + modv_off((P >> 2) & 1, 576 + 288 * r + tid) + ((P >> 3) & 1) * 4096);
    }
    bar_sync(14, 320);
    mbar_wait(BAR(B_CX), 0);
    TS0(39);
    uint32_t cw[8];
    if (is_red) {
        uint32_t cz[4];
#pragma unroll
        for (int s = 0; s < 4; s++) cz[s] = lds32(sb + OFF_C + (g & 3) * 1152 + w * 128 + (g & 4) * 16 + ((s + g) & 3) * 16 + t * 4);
#pragma unroll
        for (int s = 0; s < 4; s++) cz[s] = pack2(silu(bf_lo(cz[s])), silu(bf_hi(cz[s])));
        if (g & 1) { const uint32_t z = cz[3]; cz[3] = cz[2]; cz[2] = cz[1]; cz[1] = cz[0]; cz[0] = z; }
        if (g & 2) { uint32_t z = cz[0]; cz[0] = cz[2]; cz[2] = z; z = cz[1]; cz[1] = cz[3]; cz[3] = z; }
#pragma unroll
        for (int s = 0; s < 4; s++) {
            const uint32_t o = __shfl_xor_sync(~0u, cz[s], 16);
            cw[s] = (g & 4) ? o : cz[s];
            cw[4 + s] = (g & 4) ? cz[s] : o;
        }
    }

    if (is_red) {
        asm volatile("cp.async.wait_all;" ::: "memory");
        __syncwarp();
        TSM(1);
        float d[4] = {0.f, 0.f, 0.f, 0.f}, e[4] = {0.f, 0.f, 0.f, 0.f};
        uint32_t a[4][4];
#pragma unroll
        for (int s = 0; s < 4; s++)
            ldsm4t(a[s], sb + OFF_MOD0 + (64 * w + 16 * s + (i4 >> 1) * 8 + rho) * 32 + (((i4 ^ (rho >> 2)) & 1) << 4));
        mma(d, a[0], cw[0], cw[1]);
        mma(e, a[1], cw[2], cw[3]);
        mma(d, a[2], cw[4], cw[5]);
        mma(e, a[3], cw[6], cw[7]);
        sts64f(sb + OFF_RED + ((w * 16 + (t >> 1) * 8 + g) * 4 + (t & 1) * 2) * 4, t < 2 ? d[0] + e[0] : d[2] + e[2], t < 2 ? d[1] + e[1] : d[3] + e[3]);
        if (w >= 2) {
            bar_arrive(1, 288);
        } else {
            bar_all();
            float4 v[9];
#pragma unroll
            for (int i = 0; i < 9; i++) v[i] = lds128f(sb + OFF_RED + i * 256 + (lane & 15) * 16);
            const float s0 = (((v[0].x + v[1].x) + (v[2].x + v[3].x)) + ((v[4].x + v[5].x) + (v[6].x + v[7].x))) + v[8].x;
            const float s1 = (((v[0].y + v[1].y) + (v[2].y + v[3].y)) + ((v[4].y + v[5].y) + (v[6].y + v[7].y))) + v[8].y;
            const float s2 = (((v[0].z + v[1].z) + (v[2].z + v[3].z)) + ((v[4].z + v[5].z) + (v[6].z + v[7].z))) + v[8].z;
            const float s3 = (((v[0].w + v[1].w) + (v[2].w + v[3].w)) + ((v[4].w + v[5].w) + (v[6].w + v[7].w))) + v[8].w;
            st_pub2(gb + modv_off(w, 16 * j + (lane & 15)) + (lane >> 4) * 4096, pack2_tag(s0, s1, ((ep_raw + 1) & 1u) << 16), pack2(s2, s3));
            TS0(2);
        }
        __syncwarp();
        sts128(sb + OFF_MOD0 + w * 2048 + lane * 16, (g & 4) ? cw[4] : cw[0], (g & 4) ? cw[5] : cw[1], (g & 4) ? cw[6] : cw[2], (g & 4) ? cw[7] : cw[3]);
    }
    uint32_t xc[4];
#pragma unroll
    for (int b = 0; b < 4; b++) xc[b] = lds16(sb + OFF_X + b * 1152 + (288 * r + tid) * 2);
    if (is_red && w == 0) {
        const uint32_t xa = sb + OFF_X + (8 * j + (lane & 7)) * 2;
        if (lane < 8) sts64(sb + OFF_XO + lane * 8, lds16(xa) | (lds16(xa + 1152) << 16), lds16(xa + 2304) | (lds16(xa + 3456) << 16));
    }
    __syncwarp();
    asm volatile("barrier.cluster.arrive.relaxed.aligned;" ::: "memory");
    bar_sync(4, NTHR);
    const uint32_t side = lds32(sb + OFF_SIDE), par = parity(), par16 = par << 16;
    const char* sasrc = gb + sided(modv_off(rep, 288 * r + tid), side);
    const char* casrc = gb + sided(modv_off(rep, 576 + 288 * r + tid), side);
    if (is_red) { sav = ld_poll2(sasrc); cav = ld_poll2(casrc); }
    TS0(3);

    {
        const float4 mu = lds128f(sb + OFF_LN1), rs = lds128f(sb + OFF_LN1 + 16);
        const float n0 = (bf_lo(xc[0]) - mu.x) * rs.x, n1 = (bf_lo(xc[1]) - mu.y) * rs.y;
        const float n2 = (bf_lo(xc[2]) - mu.z) * rs.z, n3 = (bf_lo(xc[3]) - mu.w) * rs.w;
        uint32_t a[9][4];
        const int kh = w >> 2, mt = w & 3;
        const uint32_t wqa = sb + OFF_WQ + (144 * kh + (i4 >> 1) * 8 + rho) * 128 + (((2 * mt + (i4 & 1)) ^ rho) << 4);
        bool have = w == 8;
        uint32_t n = 0;
        while (!__all_sync(~0u, (((sav.x ^ par) | (cav.x ^ par)) & 1u) == 0)) {
            sav = ld_poll2(sasrc);
            cav = ld_poll2(casrc);
            if (!have && __all_sync(~0u, mbar_test(BAR(B_WQ + 2 * kh + (lane & 1)), 0))) {
                have = true;
#pragma unroll
                for (int s = 0; s < 9; s++) ldsm4t(a[s], wqa + s * 2048);
            }
            SPIN_GUARD(n);
        }
        const uint32_t ha = sb + OFF_HS + tid * 2;
        sts16(ha, pack2(n0 * (1.f + bf_lo(cav.x)) + bf_lo(sav.x), 0.f));
        sts16(ha + 1168, pack2(n1 * (1.f + bf_hi(cav.x)) + bf_hi(sav.x), 0.f));
        sts16(ha + 2336, pack2(n2 * (1.f + bf_lo(cav.y)) + bf_lo(sav.y), 0.f));
        sts16(ha + 3504, pack2(n3 * (1.f + bf_hi(cav.y)) + bf_hi(sav.y), 0.f));
        TSM(4);
        asm volatile("barrier.cluster.wait.aligned;" ::: "memory");
        if (!have) {
            mbar_wait_n(BAR(B_WQ + 2 * kh), 2, lane);
#pragma unroll
            for (int s = 0; s < 9; s++) ldsm4t(a[s], wqa + s * 2048);
        }
        bar_all();
        TS0(5);
        if (w < 8) {
            float d0[4] = {0.f, 0.f, 0.f, 0.f}, d1[4] = {0.f, 0.f, 0.f, 0.f}, d2[4] = {0.f, 0.f, 0.f, 0.f};
            const uint32_t hb = sb + OFF_HS + (g & 3) * 1168 + (144 * kh + 2 * t) * 2;
#pragma unroll
            for (int s = 0; s < 9; s += 3) {
                mma(d0, a[s], lds32(hb + s * 32), lds32(hb + s * 32 + 16));
                mma(d1, a[s + 1], lds32(hb + s * 32 + 32), lds32(hb + s * 32 + 48));
                mma(d2, a[s + 2], lds32(hb + s * 32 + 64), lds32(hb + s * 32 + 80));
            }
            const float v0 = t < 2 ? d0[0] + d1[0] + d2[0] : d0[2] + d1[2] + d2[2];
            const float v1 = t < 2 ? d0[1] + d1[1] + d2[1] : d0[3] + d1[3] + d2[3];
            const uint32_t qa = sb + OFF_SP + ((2 * r + kh) * 256 + (16 * mt + (t >> 1) * 8 + g) * 4 + (t & 1) * 2) * 4;
            st_async2(mapa(qa, peer), v0, v1, mapa(BAR(B_QP), peer));
            sts64f(qa, v0, v1);
            __syncwarp();
            if (lane == 0) mbar_arrive(BAR(B_QP));
            TS0(6);
        } else if (lane == 0) {
            mbar_arrive(BAR(B_FREE_WQ));
        }
    }

    if (w < 8) {
        uint32_t bq[4][2][4];
        auto load_wuk = [&]() {
#pragma unroll
            for (int jj = 0; jj < 2; jj++)
#pragma unroll
                for (int i = 0; i < 4; i++) {
                    const int rl = 2 * ((i + (rho >> 1)) & 3) + (rho & 1);
                    ldsm4(bq[i][jj], sb + OFF_WUK + (32 * w + 8 * (rho >> 1) + rl) * 128 + (((4 * jj + i4) ^ rl) << 4));
                }
        };
        const bool have = mbar_test(BAR(B_WUK + (w >> 1)), 0);
        if (have) load_wuk();
        mbar_wait(BAR(B_QP), 0);
        TS0(7);
        const uint32_t qa = sb + OFF_SP + tid * 4;
        const float qs = (ldsf(qa) + ldsf(qa + 1024)) + (ldsf(qa + 2048) + ldsf(qa + 3072));
        sts16(sb + OFF_ACT + (tid & 3) * 144 + (tid >> 2) * 2, pack2(qs, 0.f));
        bar_sync(2, 256);
        const uint32_t ab = sb + OFF_ACT + (g & 3) * 144 + t * 4;
        uint32_t aq[8];
#pragma unroll
        for (int s = 0; s < 8; s++) aq[s] = lds32(ab + s * 16);
        if (!have) {
            mbar_wait(BAR(B_WUK + (w >> 1)), 0);
            load_wuk();
        }
        TSM(8);
        float d[4][4];
#pragma unroll
        for (int i = 0; i < 4; i++) { d[i][0] = d[i][1] = d[i][2] = d[i][3] = 0.f; }
#pragma unroll
        for (int s = 0; s < 4; s++)
#pragma unroll
            for (int i = 0; i < 4; i++) mma(d[i], aq[2 * s], 0u, aq[2 * s + 1], 0u, bq[i][s >> 1][(s & 1) * 2], bq[i][s >> 1][(s & 1) * 2 + 1]);
        const float sc = 0.08838834764831845f * 1.4426950408889634f;
        uint32_t u[4];
#pragma unroll
        for (int i = 0; i < 4; i++) {
            const float lo = d[i][0] * sc, hi = d[i][1] * sc;
            u[i] = ((i + t) & 1) ? pack2(lo, hi) : pack2_tag(lo, hi, par16);
        }
        if (t & 1) { const uint32_t z = u[3]; u[3] = u[2]; u[2] = u[1]; u[1] = u[0]; u[0] = z; }
        if (t & 2) { uint32_t z = u[0]; u[0] = u[2]; u[2] = z; z = u[1]; u[1] = u[3]; u[3] = z; }
        st_pub4(gb + G_QABS + ((g & 3) * 2 + r) * 65536 + (g >> 2) * 4096 +
                    dup32((p * 1024 + ((w >> 1) & 1) * 512 + ((w >> 2) * 32 + h) * 8 + (((w & 1) * 4 + t) ^ (h & 7))) * 16),
                u[0], u[1], u[2], u[3]);
        __syncwarp();
        bar_arrive(1, 288);
    } else {
        bar_all();
        if (lane < 8) red_add(gb + G_CNT + (lane & 1) * 4096 + (r * 4 + (lane >> 1)) * 128, 1);
        if (lane == 0) mbar_arrive_remote(mapa(BAR(B_PEER_WUK), peer));
        if (lane == 0) TS(9);
        __syncwarp();
    }
    }

    {
        uint32_t phase = 0;
        while (true) {
            bool bad = false;
            if (w < 8) {
                mbar_wait(BAR(B_QABS), phase & 1);
                TS0(11);
                uint32_t va = ~0u, vo = 0u;
                uint4 u0[4], u1[4];
#pragma unroll
                for (int i = 0; i < 4; i++) {
                    u0[i] = lds128(sb + OFF_WQ + (i * 256 + tid) * 16);
                    u1[i] = lds128(sb + OFF_WQ + 16384 + (i * 256 + tid) * 16);
                }
#pragma unroll
                for (int i = 0; i < 4; i++) {
                    va &= u0[i].x & u0[i].z & u1[i].x & u1[i].z;
                    vo |= u0[i].x | u0[i].z | u1[i].x | u1[i].z;
                    sts128(sb + OFF_MOD0 + (i * 256 + tid) * 16, hadd2(u0[i].x, u1[i].x), hadd2(u0[i].y, u1[i].y),
                           hadd2(u0[i].z, u1[i].z), hadd2(u0[i].w, u1[i].w));
                }
                fence_async();
                bad = ((parity() ? va : ~vo) & 1u) == 0;
            }
            __syncwarp();
            if (bar_and(3, 384, !bad)) break;
            SPIN_GUARD(phase);
            if (w == 0) {
                TS(46);
                if (lane == 0) mbar_arrive_tx(BAR(B_QABS), 32768);
                fetch_qabs();
            }
        }
        TS0(12);
        const uint32_t sbu = __shfl_sync(~0u, sb & 0x3FFFFu, 0);
        if (w < 4) {
            float o[4][16];
#pragma unroll
            for (int m = 0; m < 4; m++)
#pragma unroll
                for (int i = 0; i < 16; i++) o[m][i] = 0.f;
            auto step = [&](int tile, auto NT) {
                constexpr int nt = decltype(NT)::value;
                const uint32_t da = desc_lo(sbu + OFF_CKV + tile * 16384, 16);
                const uint32_t dp = desc_lo(sbu + OFF_SX + tile * 4096, 128);
                mbar_wait(BAR(B_PF + tile), 0);
                float2 al[4];
#pragma unroll
                for (int i = 0; i < 4; i++) al[i] = lds64f(sb + OFF_SX + tile * 4096 + i * 1024 + 512 + t * 32);
#pragma unroll
                for (int m = 0; m < 4; m++)
#pragma unroll
                    for (int i = 0; i < 16; i++) o[m][i] *= (i & 1) ? al[i >> 2].y : al[i >> 2].x;
#pragma unroll
                for (int m = 0; m < 4; m++) pin(o[m]);
                TS0(48 + tile);
                wg_fence();
#pragma unroll
                for (int ks = 0; ks < 2 * nt; ks++)
#pragma unroll
                    for (int m = 0; m < 4; m++)
                        wgmma_pv(o[m], da + (ks >> 1) * 1024 + (m & 1) * 512 + (m >> 1) * 64 + (ks & 1) * 256, dp + (ks >> 1) * 256 + (ks & 1) * 16);
                wg_commit();
                wg_wait0();
#pragma unroll
                for (int m = 0; m < 4; m++) pin(o[m]);
            };
#pragma unroll 1
            for (int tile = 0; tile < 6; tile += 2) {
                step(tile, IC<2>());
                if (lane == 0 && tile != 2) mbar_arrive(BAR(B_FREE_T1 + (tile >> 2)));
            }
#pragma unroll 1
            for (int tile = 6; tile < 8; tile++) step(tile, IC<1>());
            TS0(13);
            if (lane == 0) mbar_arrive(BAR(B_FREE_RING));
            mbar_wait(BAR(B_TAB), 0);
            const uint32_t par16 = parity() << 16;
            const uint32_t ma = lds32(sb + OFF_SIDE + 8), md = ma ^ lds32(sb + OFF_SIDE + 12);
            const uint32_t rowo = G_INB + dup32(P * 512 + (((w * 8 + g) ^ (P & 7)) << 4));
#pragma unroll
            for (int v = 0; v < 8; v++) {
                const int e0 = (v >> 1) * 4 + (v & 1), hl = 2 * (t ^ (v >> 1)) + (v & 1), hh = 8 * (v >> 1) + hl;
                const uint32_t off = sided((1 + (v >> 1)) * PAGE + (hl * 2 + r) * 65536 + rowo, ma >> hh);
                const uint32_t u0 = pack2_tag(o[0][e0], o[0][e0 + 2], par16), u1 = pack2(o[1][e0], o[1][e0 + 2]);
                const uint32_t u2 = pack2_tag(o[2][e0], o[2][e0 + 2], par16), u3 = pack2(o[3][e0], o[3][e0 + 2]);
                st_pub4(gb + off, u0, u1, u2, u3);
                if ((md >> hh) & 1u) st_pub4(gb + (off ^ 4096u), u0, u1, u2, u3);
            }
            __syncwarp();
            bar_arrive(10, 256);
        } else if (w < 8) {
            const int wl = w & 3;
            const uint32_t dq = desc_lo(sbu + OFF_MOD0, 16);
            const uint32_t xo_ = (wl * 8 + g) * 128 + ((t ^ wl) << 5) + ((g & 1) << 4);
            uint32_t fail = 0;
            auto send = [&](const float (&s)[32], int tile, int btile) {
                const uint32_t sxr = mapa(sb + OFF_SX + tile * 4096 + xo_, peer), sbr = mapa(BAR(B_SX + btile), peer);
                const uint32_t sl = sb + OFF_SL + (tile & 3) * 4096 + xo_;
                float y[8];
#pragma unroll
                for (int i = 0; i < 4; i++) {
                    const float lo = s[(i >> 1) * 4 + (i & 1)] + s[16 + (i >> 1) * 4 + 2 + (i & 1)];
                    const float hi = s[8 + (i >> 1) * 4 + (i & 1)] + s[24 + (i >> 1) * 4 + 2 + (i & 1)];
                    y[i] = (g & 1) ? hi : lo;
                    y[4 + i] = (g & 1) ? lo : hi;
                }
                st_async4(sxr, y[0], y[1], y[2], y[3], sbr);
                st_async4(sxr ^ 16, y[4], y[5], y[6], y[7], sbr);
                sts128f(sl, y[0], y[1], y[2], y[3]);
                sts128f(sl ^ 16, y[4], y[5], y[6], y[7]);
            };
            mbar_wait(BAR(B_PEER_WUK), 0);
#pragma unroll 1
            for (int tile = 0; tile < 6; tile += 2) {
                const uint32_t da = desc_lo(sbu + OFF_CKV + tile * 16384, 16);
                float s0[32], s1[32];
                mbar_wait_n(BAR(B_CKV + 2 * tile), 4, lane);
                wg_fence();
                wgmma_s<0>(s0, da, dq);
#pragma unroll
                for (int kk = 1; kk < 8; kk++) wgmma_s<1>(s0, da + (kk >> 2) * 512 + (kk & 3) * 2, dq + (kk >> 2) * 512 + (kk & 3) * 2);
                wg_commit();
                wgmma_s<0>(s1, da + 1024, dq);
#pragma unroll
                for (int kk = 1; kk < 8; kk++) wgmma_s<1>(s1, da + 1024 + (kk >> 2) * 512 + (kk & 3) * 2, dq + (kk >> 2) * 512 + (kk & 3) * 2);
                wg_commit();
                TSA(56 + tile);
                if (tile == 4) bar_sync(5, 256);
                asm volatile("wgmma.wait_group.sync.aligned 1;" ::: "memory");
                pin(s0);
                send(s0, tile, tile);
                wg_wait0();
                pin(s1);
                send(s1, tile + 1, tile);
                __syncwarp();
                if (lane == 0) mbar_arrive(BAR(B_SX + tile));
            }
            bar_sync(6, 256);
#pragma unroll 1
            for (int tile = 6; tile < 8; tile++) {
                const uint32_t da = desc_lo(sbu + OFF_CKV + tile * 16384, 16);
                float s[32];
                fail |= mbar_wait_nt(BAR(B_CKV + 2 * tile), 0);
                wg_fence();
                wgmma_s<0>(s, da, dq);
#pragma unroll
                for (int kk = 1; kk < 4; kk++) wgmma_s<1>(s, da + kk * 2, dq + kk * 2);
                fail |= mbar_wait_nt(BAR(B_CKV + 2 * tile + 1), 0);
                wg_fence();
#pragma unroll
                for (int kk = 0; kk < 4; kk++) wgmma_s<1>(s, da + 512 + kk * 2, dq + 512 + kk * 2);
                wg_commit();
                TSA(56 + tile);
                wg_wait0();
                pin(s);
                send(s, tile, tile);
                __syncwarp();
                if (lane == 0) mbar_arrive(BAR(B_SX + tile));
            }
            if (fail) __trap();
        } else {
            const int wl = w & 3, head = 8 * (g >> 1) + 2 * wl + (g & 1);
            const uint32_t ro = t * 1024 + ((wl ^ t) * 8 + g) * 4;
            const uint32_t po = (g >> 1) * 1024 + ((wl ^ (g >> 1)) << 5);
            float mrun = -INFINITY, lrun = 0.f;
            auto step = [&](int tile, auto NT) {
                constexpr int n = 8 * decltype(NT)::value;
                mbar_wait(BAR(B_SX + tile), 0);
                float ua[n], ub[n], v[n];
#pragma unroll
                for (int i = 0; i < n; i++) {
                    ua[i] = ldsf(sb + OFF_SX + tile * 4096 + ro + (i >> 3) * 4096 + (i & 7) * 128);
                    ub[i] = ldsf(sb + OFF_SL + (tile & 3) * 4096 + ro + (i >> 3) * 4096 + (i & 7) * 128);
                }
#pragma unroll
                for (int i = 0; i < n; i++) v[i] = ua[i] + ub[i];
                float mx = fmaxf(fmaxf(fmaxf(v[0], v[1]), fmaxf(v[2], v[3])), fmaxf(fmaxf(v[4], v[5]), fmaxf(v[6], v[7])));
                if (n == 16) mx = fmaxf(mx, fmaxf(fmaxf(fmaxf(v[n - 8], v[n - 7]), fmaxf(v[n - 6], v[n - 5])), fmaxf(fmaxf(v[n - 4], v[n - 3]), fmaxf(v[n - 2], v[n - 1]))));
                const float m1 = shfl_xor_v(mx, 1), m2 = shfl_xor_v(mx, 2), m3 = shfl_xor_v(mx, 3);
                const float mn = fmaxf(fmaxf(fmaxf(mx, mrun), m1), fmaxf(m2, m3));
                const float al = ex2(mrun - mn);
                mrun = mn;
                const uint32_t pa = sb + OFF_SX + tile * 4096 + po;
                float ls = 0.f;
#pragma unroll
                for (int q = 0; q < n; q += 8) {
#pragma unroll
                    for (int i = q; i < q + 8; i++) v[i] = ex2(v[i] - mn);
                    sts128(pa + q * 512 + t * 128 + (g & 1) * 16, pack2(v[q], v[q + 1]), pack2(v[q + 2], v[q + 3]), pack2(v[q + 4], v[q + 5]), pack2(v[q + 6], v[q + 7]));
                    ls += ((v[q] + v[q + 1]) + (v[q + 2] + v[q + 3])) + ((v[q + 4] + v[q + 5]) + (v[q + 6] + v[q + 7]));
                }
                if (t == 0) stsf(pa + 512 + (g & 1) * 4, al);
                fence_async();
                __syncwarp();
                if (lane == 0) mbar_arrive(BAR(B_PF + tile));
                lrun = lrun * al + ls;
            };
#pragma unroll 1
            for (int tile = 0; tile < 6; tile += 2) {
                step(tile, IC<2>());
                if (tile < 4) bar_arrive(5 + (tile >> 1), 256);
            }
#pragma unroll 1
            for (int tile = 6; tile < 8; tile++) step(tile, IC<1>());
            lrun += __shfl_xor_sync(~0u, lrun, 1);
            lrun += __shfl_xor_sync(~0u, lrun, 2);
            {
                const uint32_t mt_ = (__float_as_uint(mrun) & ~1u) | parity(), lt_ = __float_as_uint(lrun);
                st_pub4(gb + (1 + (head >> 3)) * PAGE + G_STAT + dup(((head & 7) * 2 + r) * 2048 + P * 32 + (t & 1) * 16) + (t >> 1) * 4096,
                        mt_, lt_, mt_, lt_);
            }
            __syncwarp();
            if (w == 10) {
                bar_sync(10, 256);
                if (lane < 8) red_add(gb + G_CNT + 1024 + (lane & 1) * 4096 + (r * 4 + (lane >> 1)) * 128, 1);
                if (lane == 0) TS(14);
            } else {
                bar_arrive(10, 256);
            }
            if (w >= 9) return;
        }
    }

    uint32_t awo[2][4][4];
    bool have_wo = false;
    if (w < 8) {
        uint32_t av[2][4][4];
        mbar_wait_n(BAR(B_WUV), 4, lane);
#pragma unroll
        for (int s = 0; s < 2; s++) {
            const int rl = 4 * (w & 1) + ((2 * s + (i4 >> 1) + (rho >> 1)) & 3);
            const int row = 64 * (rho >> 1) + 16 * (w >> 1) + 8 * (rho & 1) + rl;
#pragma unroll
            for (int mt = 0; mt < 4; mt++) ldsm4t(av[s][mt], sb + OFF_WUV + row * 128 + (((2 * mt + (i4 & 1)) ^ rl) << 4));
        }
        __syncwarp();
        if (lane == 0) mbar_arrive(BAR(B_FREE_WUV));
        TS0(35);
        {
            uint32_t n = 0;
            while (true) {
                const uint32_t m = __ballot_sync(~0u, mbar_test(lane < 4 ? BAR(B_WO + lane) : BAR(B_INB3), 0));
                if (m & 16u) break;
                if ((m & 15u) == 15u) {
                    load_wide_frags(awo[0], sb + OFF_WQ, 0, w, lane);
                    load_wide_frags(awo[1], sb + OFF_WQ, 1, w, lane);
                    have_wo = true;
                    break;
                }
                if (++n > (1u << 24)) __trap();
            }
        }
        float dc[4][4];
        const uint32_t par = parity();
        uint32_t phase = 0;
        while (true) {
            mbar_wait(BAR(B_INB3), phase & 1);
            TS0(16);
            const uint32_t sa = sb + OFF_STAT + ((g & 3) * 16 + t) * 32 + (g & 3) * 8;
            const float2 e0 = lds64f(sa), e1 = lds64f(sa + 128), e2 = lds64f(sa + 256), e3 = lds64f(sa + 384);
            uint32_t bo[4][2][4];
            const int rl = (rho >> 1) + 4 * (rho & 1);
#pragma unroll
            for (int jj = 0; jj < 2; jj++)
#pragma unroll
                for (int nt = 0; nt < 4; nt++)
                    ldsm4t(bo[nt][jj], sb + OFF_INBOX3 + (32 * jj + 8 * i4 + rl) * 512 + (((4 * w + nt) ^ rl) << 4));
            float M = fmaxf(fmaxf(e0.x, e1.x), fmaxf(e2.x, e3.x));
            M = fmaxf(M, __shfl_xor_sync(~0u, M, 1));
            M = fmaxf(M, __shfl_xor_sync(~0u, M, 2));
            const float w0 = ex2(e0.x - M), w1 = ex2(e1.x - M), w2 = ex2(e2.x - M), w3 = ex2(e3.x - M);
            const uint32_t wa = pack2(w0, w1), wb = pack2(w2, w3);
            float L = (bf_lo(wa) * e0.y + bf_hi(wa) * e1.y) + (bf_lo(wb) * e2.y + bf_hi(wb) * e3.y);
            L += __shfl_xor_sync(~0u, L, 1);
            L += __shfl_xor_sync(~0u, L, 2);
            const float inv = rcp(L);
            uint32_t va = ~0u, vo = 0u;
#pragma unroll
            for (int nt = 0; nt < 4; nt++) dc[nt][0] = dc[nt][1] = dc[nt][2] = dc[nt][3] = 0.f;
#pragma unroll
            for (int s = 0; s < 4; s++) {
                const bool mine = (g & 3) == s;
#pragma unroll
                for (int nt = 0; nt < 4; nt++) {
                    const uint32_t b0 = bo[nt][s >> 1][(s & 1) * 2], b1 = bo[nt][s >> 1][(s & 1) * 2 + 1];
                    va &= b0 & b1;
                    vo |= b0 | b1;
                    mma(dc[nt], mine ? wa : 0u, 0u, mine ? wb : 0u, 0u, b0, b1);
                }
            }
#pragma unroll
            for (int nt = 0; nt < 4; nt++) { dc[nt][0] *= inv; dc[nt][1] *= inv; }
            const uint32_t sa_ = __float_as_uint(e0.x) & __float_as_uint(e1.x) & __float_as_uint(e2.x) & __float_as_uint(e3.x);
            const uint32_t so_ = __float_as_uint(e0.x) | __float_as_uint(e1.x) | __float_as_uint(e2.x) | __float_as_uint(e3.x);
            const bool bad = (((par ? sa_ : ~so_) & 1u) == 0) || ((g & 3) == 0 && ((par ? va : ~vo) & 0x10001u) != 0x10001u);
            if (!bar8_or(bad)) break;
            SPIN_GUARD(phase);
            if (w == 0) {
                TS(47);
                if (lane == 0) mbar_arrive_tx(BAR(B_INB3), INB3_BYTES);
                fetch_inbox();
            }
        }
        TS0(17);
        uint32_t u[4];
#pragma unroll
        for (int nt = 0; nt < 4; nt++) u[nt] = pack2(dc[nt][0], dc[nt][1]);
        if (t & 1) { const uint32_t z = u[0]; u[0] = u[1]; u[1] = u[2]; u[2] = u[3]; u[3] = z; }
        if (t & 2) { uint32_t z = u[0]; u[0] = u[2]; u[2] = z; z = u[1]; u[1] = u[3]; u[3] = z; }
        float d[4][4];
#pragma unroll
        for (int mt = 0; mt < 4; mt++) {
            d[mt][0] = d[mt][1] = d[mt][2] = d[mt][3] = 0.f;
            mma(d[mt], av[0][mt], u[0], u[1]);
        }
#pragma unroll
        for (int mt = 0; mt < 4; mt++) mma(d[mt], av[1][mt], u[2], u[3]);
        const uint32_t ca = sb + OFF_CP + (r * 8 + w) * 512 + (((t >> 1) * 8 + g) * 4 + (t & 1) * 2) * 4;
        const uint32_t cr = mapa(ca, peer), cbar = mapa(BAR(B_CP), peer);
#pragma unroll
        for (int m2 = 0; m2 < 2; m2++) {
            const float a0 = t < 2 ? d[m2][0] : d[m2][2], a1 = t < 2 ? d[m2][1] : d[m2][3];
            const float b0 = t < 2 ? d[2 + m2][0] : d[2 + m2][2], b1 = t < 2 ? d[2 + m2][1] : d[2 + m2][3];
            st_async2(cr + m2 * 256, r ? a0 : b0, r ? a1 : b1, cbar);
            sts64f(ca + m2 * 256, r ? b0 : a0, r ? b1 : a1);
        }
        __syncwarp();
        if (lane == 0) mbar_arrive(BAR(B_CP));
        if (tid == 160) mbar_arrive(BAR(B_FREE_INB3));
    }

    {
        if (!have_wo) {
            mbar_wait_n(BAR(B_WO), 4, lane);
            load_wide_frags(awo[0], sb + OFF_WQ, 0, w, lane);
            load_wide_frags(awo[1], sb + OFF_WQ, 1, w, lane);
        }
        __syncwarp();
        if (lane == 0) mbar_arrive(BAR(B_FREE_WO));
        TS0(36);
        mbar_wait(BAR(B_TAB), 0);
        uint32_t po[4];
        partial_slots(po, sb, id, w, lane);
        if (w < 4) {
            mbar_wait(BAR(B_CP), 0);
            TS0(18);
            float v[16];
#pragma unroll
            for (int i = 0; i < 16; i++) v[i] = ldsf(sb + OFF_CP + i * 512 + tid * 4);
            const float cs = (((v[0] + v[1]) + (v[2] + v[3])) + ((v[4] + v[5]) + (v[6] + v[7]))) +
                             (((v[8] + v[9]) + (v[10] + v[11])) + ((v[12] + v[13]) + (v[14] + v[15])));
            sts16(sb + OFF_ACT + (tid & 3) * 144 + (tid >> 2) * 2, pack2(cs, 0.f));
        }
        bar_all();
        const uint32_t ab = sb + OFF_ACT + (g & 3) * 144 + t * 4;
        const uint32_t b0 = lds32(ab), b1 = lds32(ab + 16), b2 = lds32(ab + 32), b3 = lds32(ab + 48);
        float d[4][4];
#pragma unroll
        for (int mt = 0; mt < 4; mt++) {
            d[mt][0] = d[mt][1] = d[mt][2] = d[mt][3] = 0.f;
            mma(d[mt], awo[0][mt], b0, b1);
        }
#pragma unroll
        for (int mt = 0; mt < 4; mt++) mma(d[mt], awo[1][mt], b2, b3);
        send_partials(gb, po, d, lane, 0x10000u);
        TSM(19);
    }

    const uint32_t side = lds32(sb + OFF_SIDE), par = parity(), par16 = par << 16;
    const uint32_t sbo = sided(modv_off(rep, 3 * 576 + 2 * tid), side), cbo = sided(modv_off(rep, 4 * 576 + 2 * tid), side);
    uint4 sbv = ld_poll4(gb + sbo), cbv = ld_poll4(gb + cbo);

    float x2own = 0.f, gbown = 0.f;
    if (is_red) {
        uint2 gav, gbv;
        if (w == 0) {
            gav = ld_poll2(gb + sided(modv_off(rep, 2 * 576 + 8 * j + rho), side));
            gbv = ld_poll2(gb + sided(modv_off(rep, 5 * 576 + 8 * j + rho), side));
        }
        const float4 att = reduce_partials(gb, j, side, 1u, sb, tid, w, lane, 20);
        if (w == 0) {
            uint32_t n = 0;
            while (!__all_sync(~0u, (((gav.x ^ par) | (gbv.x ^ par)) & 1u) == 0)) {
                gav = ld_poll2(gb + sided(modv_off(rep, 2 * 576 + 8 * j + rho), side));
                gbv = ld_poll2(gb + sided(modv_off(rep, 5 * 576 + 8 * j + rho), side));
                SPIN_GUARD(n);
            }
            const uint32_t xo0 = lds32(sb + OFF_XO + rho * 8), xo1 = lds32(sb + OFF_XO + rho * 8 + 4);
            const float y0 = bf_lo(xo0) + bf_lo(gav.x) * att.x, y1 = bf_hi(xo0) + bf_hi(gav.x) * att.y;
            const float y2 = bf_lo(xo1) + bf_lo(gav.y) * att.z, y3 = bf_hi(xo1) + bf_hi(gav.y) * att.w;
            st_pub2(gb + modv_off(lane >> 4, 6 * 576 + 8 * j + rho) + (i4 & 1) * 4096, pack2_tag(y0, y1, par16), pack2(y2, y3));
            TS0(21);
            x2own = i4 == 0 ? y0 : i4 == 1 ? y1 : i4 == 2 ? y2 : y3;
            gbown = i4 == 0 ? bf_lo(gbv.x) : i4 == 1 ? bf_hi(gbv.x) : i4 == 2 ? bf_lo(gbv.y) : bf_hi(gbv.y);
        }
    }

    {
        const uint32_t pitch = heavy ? 96u : 64u;
        const uint32_t gub = sb + OFF_RINGE - (w + 1) * 2 * gubox + ((i4 >> 1) * 8 + rho) * pitch;
        const uint32_t xr = heavy ? 0u : (uint32_t)(rho >> 1);
        uint32_t ag[2][4][4], au[2][4][4];
        auto load_gu = [&]() {
#pragma unroll
            for (int s2 = 0; s2 < 4; s2++)
#pragma unroll
                for (int mt = 0; mt < 2; mt++) {
                    const uint32_t ab = gub + s2 * 16 * pitch + (((2 * mt + (i4 & 1)) ^ xr) << 4);
                    ldsm4t(ag[mt][s2], ab);
                    ldsm4t(au[mt][s2], ab + gubox);
                }
        };
        const float4 pv = lds128f(sb + OFF_LN1);
        const char* xsrc = gb + sided(modv_off(rep, 6 * 576 + 2 * tid), side);
        bool have = false;
        uint4 xv;
        uint32_t n = 0;
        while (true) {
            xv = ld_poll4(xsrc);
            if (!have && mbar_test(BAR(B_GU + w), 0)) {
                have = true;
                load_gu();
            }
            if (!__all_sync(~0u, (((sbv.x ^ par) | (sbv.z ^ par) | (cbv.x ^ par) | (cbv.z ^ par)) & 1u) == 0)) {
                sbv = ld_poll4(gb + sbo);
                cbv = ld_poll4(gb + cbo);
            } else if (__all_sync(~0u, (((xv.x ^ par) | (xv.z ^ par)) & 1u) == 0)) {
                break;
            }
            SPIN_GUARD(n);
        }
        TSM(22);
        const float v[8] = {bf_lo(xv.x) - pv.x, bf_hi(xv.x) - pv.y, bf_lo(xv.y) - pv.z, bf_hi(xv.y) - pv.w,
                            bf_lo(xv.z) - pv.x, bf_hi(xv.z) - pv.y, bf_lo(xv.w) - pv.z, bf_hi(xv.w) - pv.w};
        float s[8];
#pragma unroll
        for (int b = 0; b < 4; b++) { s[b] = v[b] + v[4 + b]; s[4 + b] = v[b] * v[b] + v[4 + b] * v[4 + b]; }
        {
            const bool u4 = lane & 16, u3 = lane & 8, u2 = lane & 4;
#pragma unroll
            for (int i = 0; i < 4; i++) {
                const float keep = u4 ? s[i + 4] : s[i], send = u4 ? s[i] : s[i + 4];
                s[i] = keep + __shfl_xor_sync(~0u, send, 16);
            }
#pragma unroll
            for (int i = 0; i < 2; i++) {
                const float keep = u3 ? s[i + 2] : s[i], send = u3 ? s[i] : s[i + 2];
                s[i] = keep + __shfl_xor_sync(~0u, send, 8);
            }
            const float keep = u2 ? s[1] : s[0], send = u2 ? s[0] : s[1];
            s[0] = keep + __shfl_xor_sync(~0u, send, 4);
            s[0] += __shfl_xor_sync(~0u, s[0], 1);
            s[0] += __shfl_xor_sync(~0u, s[0], 2);
            if (t == 0) stsf(sb + OFF_LNST + (w * 8 + g) * 4, s[0]);
        }
        bar_all();
        float tot;
        {
            float z[9];
#pragma unroll
            for (int i = 0; i < 9; i++) z[i] = ldsf(sb + OFF_LNST + (i * 8 + rho) * 4);
            tot = ((((z[0] + z[1]) + (z[2] + z[3])) + ((z[4] + z[5]) + (z[6] + z[7]))) + z[8]) * (1.f / 576.f);
        }
        const float oth = __shfl_xor_sync(~0u, tot, 4);
        const float mine = (lane & 4) ? rsqrtf(fmaxf(tot - oth * oth, 0.f) + 1e-5f) : tot;
        const uint32_t sw[4] = {sbv.x, sbv.y, sbv.z, sbv.w}, cwd[4] = {cbv.x, cbv.y, cbv.z, cbv.w};
#pragma unroll
        for (int b = 0; b < 4; b++) {
            const float mean = __shfl_sync(~0u, mine, b), rstd = __shfl_sync(~0u, mine, 4 + b);
            const float c0 = (b & 1) ? bf_hi(cwd[b >> 1]) : bf_lo(cwd[b >> 1]), c1 = (b & 1) ? bf_hi(cwd[2 + (b >> 1)]) : bf_lo(cwd[2 + (b >> 1)]);
            const float s0 = (b & 1) ? bf_hi(sw[b >> 1]) : bf_lo(sw[b >> 1]), s1 = (b & 1) ? bf_hi(sw[2 + (b >> 1)]) : bf_lo(sw[2 + (b >> 1)]);
            sts32(sb + OFF_HS + b * 1168 + tid * 4, pack2((v[b] - mean) * rstd * (1.f + c0) + s0, (v[4 + b] - mean) * rstd * (1.f + c1) + s1));
        }
        __syncwarp();
        uint32_t hb[8];
#pragma unroll
        for (int s2 = 0; s2 < 8; s2++) hb[s2] = lds32(sb + OFF_HS + (g & 3) * 1168 + (64 * w + 8 * s2 + 2 * t) * 2);
        TS0(23);
        if (!have) {
            mbar_wait(BAR(B_GU + w), 0);
            load_gu();
        }
        const uint32_t ra = sb + OFF_MOD0 + w * 1536 + (((t >> 1) * 8 + g) * 4 + (t & 1) * 2) * 4;
        {
            float dg[2][4], du[2][4];
#pragma unroll
            for (int mt = 0; mt < 2; mt++) { dg[mt][0] = dg[mt][1] = dg[mt][2] = dg[mt][3] = 0.f; du[mt][0] = du[mt][1] = du[mt][2] = du[mt][3] = 0.f; }
#pragma unroll
            for (int s2 = 0; s2 < 4; s2++)
#pragma unroll
                for (int mt = 0; mt < 2; mt++) {
                    mma(dg[mt], ag[mt][s2], hb[2 * s2], hb[2 * s2 + 1]);
                    mma(du[mt], au[mt][s2], hb[2 * s2], hb[2 * s2 + 1]);
                }
            if (heavy) {
#pragma unroll
                for (int s2 = 0; s2 < 4; s2++) {
                    const uint32_t ab = gub + s2 * 16 * 96 + ((4 + (i4 & 1)) << 4);
                    ldsm4t(ag[0][s2], ab);
                    ldsm4t(au[0][s2], ab + 6144);
                }
            }
#pragma unroll
            for (int mt = 0; mt < 2; mt++) {
                sts64f(ra + mt * 256, t < 2 ? dg[mt][0] : dg[mt][2], t < 2 ? dg[mt][1] : dg[mt][3]);
                sts64f(ra + 768 + mt * 256, t < 2 ? du[mt][0] : du[mt][2], t < 2 ? du[mt][1] : du[mt][3]);
            }
            if (heavy) {
#pragma unroll
                for (int mt = 0; mt < 2; mt++) { dg[mt][0] = dg[mt][1] = dg[mt][2] = dg[mt][3] = 0.f; du[mt][0] = du[mt][1] = du[mt][2] = du[mt][3] = 0.f; }
#pragma unroll
                for (int s2 = 0; s2 < 4; s2++) {
                    mma(dg[s2 & 1], ag[0][s2], hb[2 * s2], hb[2 * s2 + 1]);
                    mma(du[s2 & 1], au[0][s2], hb[2 * s2], hb[2 * s2 + 1]);
                }
                sts64f(ra + 512, t < 2 ? dg[0][0] + dg[1][0] : dg[0][2] + dg[1][2], t < 2 ? dg[0][1] + dg[1][1] : dg[0][3] + dg[1][3]);
                sts64f(ra + 768 + 512, t < 2 ? du[0][0] + du[1][0] : du[0][2] + du[1][2], t < 2 ? du[0][1] + du[1][1] : du[0][3] + du[1][3]);
            }
        }
        const int nwd = heavy ? 6 : 4;
        uint32_t ad[3][4][4];
        const bool have_d = __all_sync(~0u, mbar_test(BAR(B_WD + min(lane, nwd - 1)), 0));
        if (have_d) {
            load_wide_frags(ad[0], sb + wdbase, 0, w, lane);
            load_wide_frags(ad[1], sb + wdbase, 1, w, lane);
            if (heavy) load_wide_frags(ad[2], sb + wdbase, 2, w, lane);
        }
        bar_all();
        TS0(24);
        if (tid < nwd * 32) {
            float gz[9], uz[9];
#pragma unroll
            for (int i = 0; i < 9; i++) {
                gz[i] = ldsf(sb + OFF_MOD0 + i * 1536 + tid * 4);
                uz[i] = ldsf(sb + OFF_MOD0 + i * 1536 + 768 + tid * 4);
            }
            const float gsum = (((gz[0] + gz[1]) + (gz[2] + gz[3])) + ((gz[4] + gz[5]) + (gz[6] + gz[7]))) + gz[8];
            const float usum = (((uz[0] + uz[1]) + (uz[2] + uz[3])) + ((uz[4] + uz[5]) + (uz[6] + uz[7]))) + uz[8];
            sts16(sb + OFF_ACT + (tid & 3) * 144 + (tid >> 2) * 2, pack2(silu(gsum) * usum, 0.f));
        }
        uint32_t po[4];
        partial_slots(po, sb, id, w, lane);
        bar_all();
        TS0(25);
        const uint32_t ab = sb + OFF_ACT + (g & 3) * 144 + t * 4;
        uint32_t bd[6];
#pragma unroll
        for (int i = 0; i < 6; i++) bd[i] = lds32(ab + i * 16);
        float d[4][4];
#pragma unroll
        for (int mt = 0; mt < 4; mt++) { d[mt][0] = d[mt][1] = d[mt][2] = d[mt][3] = 0.f; }
#pragma unroll
        for (int s2 = 0; s2 < 3; s2++) {
            if (s2 < 2 || heavy) {
                if (!have_d) {
                    mbar_wait_n(BAR(B_WD + 2 * s2), 2, lane);
                    load_wide_frags(ad[s2], sb + wdbase, s2, w, lane);
                }
#pragma unroll
                for (int mt = 0; mt < 4; mt++) mma(d[mt], ad[s2][mt], bd[2 * s2], bd[2 * s2 + 1]);
            }
        }
        send_partials(gb, po, d, lane, 0u);
        TSM(26);
    }

    if (is_red) {
        const float4 ffn = reduce_partials(gb, j, side, 0u, sb, tid, w, lane, 27);
        if (w == 0) {
            const float f = i4 == 0 ? ffn.x : i4 == 1 ? ffn.y : i4 == 2 ? ffn.z : ffn.w;
            out[i4 * 576 + 8 * j + rho] = __float2bfloat16(x2own + gbown * f);
            if (id == 0 && lane == 0) red_add(gb + G_EPOCH, 1);
        }
        TS0(28);
    }
}

typedef CUresult (*EncodeFn)(CUtensorMap*, CUtensorMapDataType, cuuint32_t, void*, const cuuint64_t*, const cuuint64_t*,
                             const cuuint32_t*, const cuuint32_t*, CUtensorMapInterleave, CUtensorMapSwizzle,
                             CUtensorMapL2promotion, CUtensorMapFloatOOBfill);

void make_map(EncodeFn enc, CUtensorMap* m, const void* base, int rank, const cuuint64_t* dims, const cuuint64_t* strides,
              const cuuint32_t* box, CUtensorMapSwizzle swz) {
    cuuint32_t es[4] = {1, 1, 1, 1};
    enc(m, CU_TENSOR_MAP_DATA_TYPE_BFLOAT16, (cuuint32_t)rank, const_cast<void*>(base), dims, strides, box, es,
        CU_TENSOR_MAP_INTERLEAVE_NONE, swz, CU_TENSOR_MAP_L2_PROMOTION_L2_128B, CU_TENSOR_MAP_FLOAT_OOB_FILL_NONE);
}

void make_map2(EncodeFn enc, CUtensorMap* m, const void* base, uint64_t cols, uint64_t rows, uint32_t bc, uint32_t br,
               CUtensorMapSwizzle swz) {
    cuuint64_t dims[2] = {cols, rows}, strides[1] = {cols * 2};
    cuuint32_t box[2] = {bc, br};
    make_map(enc, m, base, 2, dims, strides, box, swz);
}

}

extern "C" void kernel_launch(void* const* d_in, const int* in_sizes, int n_in, void* d_out, int out_size) {
    (void)in_sizes; (void)n_in; (void)out_size;
    EncodeFn enc = nullptr;
    cudaDriverEntryPointQueryResult qr;
    cudaGetDriverEntryPoint("cuTensorMapEncodeTiled", (void**)&enc, cudaEnableDefault, &qr);
    Maps m;
    make_map2(enc, &m.wq, d_in[2], 4096, 576, 64, 72, CU_TENSOR_MAP_SWIZZLE_128B);
    make_map2(enc, &m.wuk, d_in[3], 4096, 512, 64, 64, CU_TENSOR_MAP_SWIZZLE_128B);
    make_map2(enc, &m.wuv, d_in[4], 4096, 512, 64, 64, CU_TENSOR_MAP_SWIZZLE_128B);
    {
        cuuint64_t dims[4] = {128, 8, 4, 2048}, strides[3] = {1024, 256, 8192};
        cuuint32_t box[4] = {64, 8, 2, 4};
        make_map(enc, &m.ckv, d_in[1], 4, dims, strides, box, CU_TENSOR_MAP_SWIZZLE_128B);
    }
    make_map2(enc, &m.wo, d_in[5], 64, 4096 * 9, 64, 72, CU_TENSOR_MAP_SWIZZLE_128B);
    make_map2(enc, &m.wd, d_in[9], 64, 4608 * 9, 64, 72, CU_TENSOR_MAP_SWIZZLE_128B);
    make_map2(enc, &m.mod, d_in[11], 3456, 576, 32, 144, CU_TENSOR_MAP_SWIZZLE_64B);
    make_map2(enc, &m.g32, d_in[7], 4608, 576, 32, 64, CU_TENSOR_MAP_SWIZZLE_64B);
    make_map2(enc, &m.u32, d_in[8], 4608, 576, 32, 64, CU_TENSOR_MAP_SWIZZLE_64B);
    make_map2(enc, &m.g48, d_in[7], 4608, 576, 48, 64, CU_TENSOR_MAP_SWIZZLE_NONE);
    make_map2(enc, &m.u48, d_in[8], 4608, 576, 48, 64, CU_TENSOR_MAP_SWIZZLE_NONE);
    cudaFuncSetAttribute(fused_kernel, cudaFuncAttributeMaxDynamicSharedMemorySize, (int)SMEM_BYTES);
    void* gs = nullptr;
    cudaGetSymbolAddress(&gs, g_scratch);
    char* gb = (char*)(((uintptr_t)gs + PAGE - 1) & ~(uintptr_t)(PAGE - 1));
    {
        cuuint64_t dims[3] = {256, 8, 5 * PAGE / 16384}, strides[2] = {2048, 16384};
        cuuint32_t box[3] = {256, 2, 4}, es[3] = {1, 1, 1};
        enc(&m.scr, CU_TENSOR_MAP_DATA_TYPE_UINT64, 3, gb, dims, strides, box, es, CU_TENSOR_MAP_INTERLEAVE_NONE,
            CU_TENSOR_MAP_SWIZZLE_NONE, CU_TENSOR_MAP_L2_PROMOTION_NONE, CU_TENSOR_MAP_FLOAT_OOB_FILL_NONE);
    }
    fused_kernel<<<NCTA, NTHR, SMEM_BYTES>>>((const __nv_bfloat16*)d_in[0], (const __nv_bfloat16*)d_in[10],
                                            (const __nv_bfloat16*)d_in[11], (__nv_bfloat16*)d_out, gb, m);
}
```

```cpp
#include <cuda_runtime.h>
#include <cuda_bf16.h>
#include <cuda.h>
#include <stdint.h>

namespace {

constexpr int NCTA = 128;
constexpr int NTHR = 512;
#define WIN 5
#define QDELAY 450
#define QPERIOD 0
#define T1POLL 2400
#define DT8 335
#define TTAIL 5700
#define NFAST 2
#define RSTBAR B_CP
#define TPROBE2 1300
#define WL 5
#define WH 4
#define TTAIL0 11200
#define TPROBE 1600
#define TSTART 250
#define RAMP 300

constexpr uint32_t OFF_CKV    = 0;
constexpr uint32_t OFF_RINGE  = 131072;
constexpr uint32_t OFF_WUV    = 0;
constexpr uint32_t OFF_MODR   = 32768;
constexpr uint32_t OFF_WUK    = 131072;
constexpr uint32_t OFF_SX     = OFF_WUK;
constexpr uint32_t OFF_WQ     = 163840;
constexpr uint32_t OFF_MOD0   = 200704;
constexpr uint32_t OFF_SP     = 219136;
constexpr uint32_t OFF_HS     = OFF_SP + 4544;
constexpr uint32_t OFF_X      = OFF_SP;
constexpr uint32_t OFF_C      = OFF_SP + 4608;
constexpr uint32_t OFF_SL     = OFF_SP;
constexpr uint32_t OFF_CP     = OFF_SP;
constexpr uint32_t OFF_RED    = OFF_SP + 9216;
constexpr uint32_t OFF_BAR    = OFF_RED + 2560;
constexpr uint32_t OFF_LN1    = OFF_BAR + 768;
constexpr uint32_t OFF_XO     = OFF_LN1 + 32;
constexpr uint32_t OFF_SIDE   = OFF_XO + 64;
constexpr uint32_t OFF_TL     = OFF_SIDE + 64;
constexpr uint32_t SMEM_BYTES = OFF_TL + 256;
constexpr uint32_t OFF_ACT    = OFF_RED + 1536;
static_assert(SMEM_BYTES <= 232448, "smem");
static_assert(OFF_RED % 128 == 0 && OFF_HS % 16 == 0 && OFF_LN1 % 16 == 0, "align");

enum {
    B_WQ = 0, B_WUK = 4, B_CKV = 8, B_WUV = 24, B_WO = 28, B_MOD = 32, B_GU = 36, B_WD = 45,
    B_FREE_CW = 51, B_FREE_MOD = 52, B_TAB = 53, B_CLR = 54, B_DONE = 55,
    B_SX = 56,
    B_CP = 64, B_QP = 65,
    B_FREE_T1 = 67, B_FREE_T4 = 68, B_FREE_RING = 69, B_PEER_SL = 70, B_FREE_SL = 71,
    B_PEER_WUK = 77, B_FREE_WUV = 78, B_FREE_INB3 = 79, B_FREE_WO = 80,
    B_CX = 95, B_COUNT = 96
};

constexpr uint32_t PAGE = 2u << 20;
constexpr uint32_t G_EPOCH = 7 * 16384, G_TAB = G_EPOCH + 8192, G_PROBE = 1966080;
constexpr uint32_t G_QABS = 262144;
constexpr uint32_t G_PART = 786432;
constexpr uint32_t G_STAT = 65536, G_INB = 131072, G_CX = 1179648;
__device__ uint4 g_scratch[6 * PAGE / 16];

__device__ __forceinline__ uint32_t dup(uint32_t l) { return ((l >> 12) << 13) | (l & 4095u); }
__device__ __forceinline__ uint32_t sided(uint32_t off, uint32_t side) { return off + (((__popc(off & 0xB2000u) ^ side) & 1u) << 12); }
__device__ __forceinline__ uint32_t stat_off(int head, int r, int P, int t) {
    return (1 + (head >> 3)) * PAGE + G_STAT + dup(((head & 7) * 2 + r) * 2048 + P * 32 + (t & 1) * 16) + (t >> 1) * 4096;
}
__device__ __forceinline__ uint32_t modv_off(int rep, int sec, int col) { return rep * 131072 + sec * 16384 + dup(col * 8); }

#define KS(k)
#define TS(k)
#define TS0(k)
#define TSA(k)
#define TSM(k)

enum { M_WQ = 0, M_WUK, M_CKV, M_WUV, M_WO, M_MOD, M_G32, M_U32, M_G48, M_U48, M_WD, M_COUNT };
struct Maps {
    CUtensorMap m[M_COUNT];
};

__device__ __forceinline__ void mbar_init(uint32_t bar, uint32_t cnt) {
    asm volatile("mbarrier.init.shared::cta.b64 [%0], %1;" ::"r"(bar), "r"(cnt) : "memory");
}
__device__ __forceinline__ void mbar_arrive_tx(uint32_t bar, uint32_t bytes) {
    asm volatile("mbarrier.arrive.expect_tx.shared::cta.b64 _, [%0], %1;" ::"r"(bar), "r"(bytes) : "memory");
}
__device__ __forceinline__ void mbar_expect_tx(uint32_t bar, uint32_t bytes) {
    asm volatile("mbarrier.expect_tx.relaxed.cta.shared::cta.b64 [%0], %1;" ::"r"(bar), "r"(bytes) : "memory");
}
__device__ __forceinline__ void mbar_arrive(uint32_t bar, uint32_t cnt = 1) {
    asm volatile("mbarrier.arrive.shared::cta.b64 _, [%0], %1;" ::"r"(bar), "r"(cnt) : "memory");
}
__device__ __forceinline__ void mbar_arrive_remote(uint32_t cbar, uint32_t cnt) {
    asm volatile("mbarrier.arrive.shared::cluster.b64 _, [%0], %1;" ::"r"(cbar), "r"(cnt) : "memory");
}
__device__ __forceinline__ bool mbar_try(uint32_t bar, uint32_t parity) {
    uint32_t ok;
    asm volatile("{\n.reg .pred p;\nmbarrier.try_wait.parity.shared::cta.b64 p, [%1], %2;\nselp.u32 %0, 1, 0, p;\n}"
                 : "=r"(ok) : "r"(bar), "r"(parity) : "memory");
    return ok != 0;
}
__device__ __forceinline__ bool mbar_test(uint32_t bar, uint32_t parity) {
    uint32_t ok;
    asm volatile("{\n.reg .pred p;\nmbarrier.test_wait.parity.shared::cta.b64 p, [%1], %2;\nselp.u32 %0, 1, 0, p;\n}"
                 : "=r"(ok) : "r"(bar), "r"(parity) : "memory");
    return ok != 0;
}
__device__ __forceinline__ void mbar_wait(uint32_t bar) {
    asm volatile("{\n.reg .pred p;\n"
                 "LAB_WAIT:\n"
                 "mbarrier.try_wait.parity.shared::cta.b64 p, [%0], 0;\n"
                 "@!p bra LAB_WAIT;\n}" ::"r"(bar) : "memory");
}
__device__ __forceinline__ void tma4d(uint32_t dst, const void* tm, int c0, int c1, int c2, int c3, uint32_t bar, uint64_t pol) {
    asm volatile("cp.async.bulk.tensor.4d.shared::cluster.global.mbarrier::complete_tx::bytes.L2::cache_hint [%0], [%1, {%3, %4, %5, %6}], [%2], %7;"
                 ::"r"(dst), "l"(tm), "r"(bar), "r"(c0), "r"(c1), "r"(c2), "r"(c3), "l"(pol) : "memory");
}
__device__ __forceinline__ void bulk_g2s(uint32_t dst, const void* src, uint32_t bytes, uint32_t bar) {
    asm volatile("cp.async.bulk.shared::cluster.global.mbarrier::complete_tx::bytes [%0], [%1], %2, [%3];"
                 ::"r"(dst), "l"(src), "r"(bytes), "r"(bar) : "memory");
}
__device__ __forceinline__ void prefetch_map(const void* tm) {
    asm volatile("prefetch.tensormap [%0];" ::"l"(tm) : "memory");
}
__device__ __forceinline__ uint32_t mapa(uint32_t a, uint32_t rank) {
    uint32_t d;
    asm("mapa.shared::cluster.u32 %0, %1, %2;" : "=r"(d) : "r"(a), "r"(rank));
    return d;
}
__device__ __forceinline__ void st_async2(uint32_t caddr, float a, float b, uint32_t cbar) {
    asm volatile("st.async.shared::cluster.mbarrier::complete_tx::bytes.v2.f32 [%0], {%1, %2}, [%3];"
                 ::"r"(caddr), "f"(a), "f"(b), "r"(cbar) : "memory");
}
__device__ __forceinline__ void st_async4(uint32_t caddr, float a, float b, float c, float d, uint32_t cbar) {
    asm volatile("st.async.shared::cluster.mbarrier::complete_tx::bytes.v4.f32 [%0], {%1, %2, %3, %4}, [%5];"
                 ::"r"(caddr), "f"(a), "f"(b), "f"(c), "f"(d), "r"(cbar) : "memory");
}
__device__ __forceinline__ void ldsm4(uint32_t (&r)[4], uint32_t a) {
    asm volatile("ldmatrix.sync.aligned.m8n8.x4.shared.b16 {%0,%1,%2,%3}, [%4];"
                 : "=r"(r[0]), "=r"(r[1]), "=r"(r[2]), "=r"(r[3]) : "r"(a) : "memory");
}
__device__ __forceinline__ void ldsm4t(uint32_t (&r)[4], uint32_t a) {
    asm volatile("ldmatrix.sync.aligned.m8n8.x4.trans.shared.b16 {%0,%1,%2,%3}, [%4];"
                 : "=r"(r[0]), "=r"(r[1]), "=r"(r[2]), "=r"(r[3]) : "r"(a) : "memory");
}
__device__ __forceinline__ void mma(float (&d)[4], uint32_t a0, uint32_t a1, uint32_t a2, uint32_t a3, uint32_t b0, uint32_t b1) {
    asm("mma.sync.aligned.m16n8k16.row.col.f32.bf16.bf16.f32 {%0,%1,%2,%3}, {%4,%5,%6,%7}, {%8,%9}, {%0,%1,%2,%3};"
        : "+f"(d[0]), "+f"(d[1]), "+f"(d[2]), "+f"(d[3]) : "r"(a0), "r"(a1), "r"(a2), "r"(a3), "r"(b0), "r"(b1));
}
__device__ __forceinline__ void mma(float (&d)[4], const uint32_t (&a)[4], uint32_t b0, uint32_t b1) {
    mma(d, a[0], a[1], a[2], a[3], b0, b1);
}
__device__ __forceinline__ constexpr uint32_t desc_hi(uint32_t sbo, uint32_t swz) { return (sbo >> 4) | (swz << 30); }
__device__ __forceinline__ uint32_t desc_lo(uint32_t addr18, uint32_t lbo) { return (addr18 >> 4) | ((lbo >> 4) << 16); }
template <int ACC>
__device__ __forceinline__ void wgmma_s(float (&d)[32], uint32_t a, uint32_t b) {
    asm volatile("{\n.reg .b64 da, db;\nmov.b64 da, {%32, %34};\nmov.b64 db, {%33, %34};\n"
                 "wgmma.mma_async.sync.aligned.m64n64k16.f32.bf16.bf16 {%0,%1,%2,%3,%4,%5,%6,%7,%8,%9,%10,%11,%12,%13,%14,%15,%16,%17,%18,%19,%20,%21,%22,%23,%24,%25,%26,%27,%28,%29,%30,%31}, da, db, %35, 1, 1, 0, 0;\n}"
                 : "+f"(d[0]), "+f"(d[1]), "+f"(d[2]), "+f"(d[3]), "+f"(d[4]), "+f"(d[5]), "+f"(d[6]), "+f"(d[7]), "+f"(d[8]), "+f"(d[9]), "+f"(d[10]), "+f"(d[11]), "+f"(d[12]), "+f"(d[13]), "+f"(d[14]), "+f"(d[15]), "+f"(d[16]), "+f"(d[17]), "+f"(d[18]), "+f"(d[19]), "+f"(d[20]), "+f"(d[21]), "+f"(d[22]), "+f"(d[23]), "+f"(d[24]), "+f"(d[25]), "+f"(d[26]), "+f"(d[27]), "+f"(d[28]), "+f"(d[29]), "+f"(d[30]), "+f"(d[31])
                 : "r"(a), "r"(b), "r"(desc_hi(1024, 1)), "n"(ACC));
}
__device__ __forceinline__ void wgmma_pv(float (&d)[16], uint32_t a, uint32_t b) {
    asm volatile("{\n.reg .b64 da, db;\nmov.b64 da, {%16, %18};\nmov.b64 db, {%17, %19};\n"
                 "wgmma.mma_async.sync.aligned.m64n32k16.f32.bf16.bf16 {%0,%1,%2,%3,%4,%5,%6,%7,%8,%9,%10,%11,%12,%13,%14,%15}, da, db, 1, 1, 1, 1, 0;\n}"
                 : "+f"(d[0]), "+f"(d[1]), "+f"(d[2]), "+f"(d[3]), "+f"(d[4]), "+f"(d[5]), "+f"(d[6]), "+f"(d[7]), "+f"(d[8]), "+f"(d[9]), "+f"(d[10]), "+f"(d[11]), "+f"(d[12]), "+f"(d[13]), "+f"(d[14]), "+f"(d[15])
                 : "r"(a), "r"(b), "r"(desc_hi(2048, 1)), "r"(desc_hi(1024, 0)));
}
__device__ __forceinline__ void wg_fence() { asm volatile("wgmma.fence.sync.aligned;" ::: "memory"); }
__device__ __forceinline__ void wg_commit() { asm volatile("wgmma.commit_group.sync.aligned;" ::: "memory"); }
__device__ __forceinline__ void wg_wait0() { asm volatile("wgmma.wait_group.sync.aligned 0;" ::: "memory"); }
__device__ __forceinline__ void fence_async() { asm volatile("fence.proxy.async.shared::cta;" ::: "memory"); }
template <int N>
__device__ __forceinline__ void pin(float (&d)[N]) {
#pragma unroll
    for (int i = 0; i < N; i++) asm volatile("" : "+f"(d[i])::"memory");
}
__device__ __forceinline__ uint32_t pack2(float lo, float hi) {
    uint32_t d;
    asm("cvt.rn.bf16x2.f32 %0, %1, %2;" : "=r"(d) : "f"(hi), "f"(lo));
    return d;
}
__device__ __forceinline__ uint32_t pack2_tag(float lo, float hi, uint32_t par16) {
    uint32_t u = ((__float_as_uint(lo) + 0x10000u - par16) & 0xFFFE0000u) | par16;
    return __byte_perm(u, pack2(0.f, hi), 0x7632);
}
__device__ __forceinline__ float bf_lo(uint32_t w) { return __uint_as_float(w << 16); }
__device__ __forceinline__ float bf_hi(uint32_t w) { return __uint_as_float(w & 0xFFFF0000u); }
__device__ __forceinline__ float rcp(float x) {
    float y;
    asm("rcp.approx.ftz.f32 %0, %1;" : "=f"(y) : "f"(x));
    return y;
}
__device__ __forceinline__ float ex2(float x) {
    float y;
    asm("ex2.approx.ftz.f32 %0, %1;" : "=f"(y) : "f"(x));
    return y;
}
__device__ __forceinline__ float silu(float x) { return x * rcp(1.f + ex2(-1.4426950408889634f * x)); }
__device__ __forceinline__ uint32_t clock_after(uint32_t dep) {
    uint32_t c;
    asm volatile("{\n.reg .pred p;\nsetp.eq.u32 p, %1, 0;\nmov.u32 %0, 0;\n@p mov.u32 %0, %clock;\n}" : "=r"(c) : "r"(dep) : "memory");
    return c;
}
__device__ __forceinline__ bool elect() {
    uint32_t p;
    asm volatile("{\n.reg .pred q;\nelect.sync _|q, 0xffffffff;\nselp.u32 %0, 1, 0, q;\n}" : "=r"(p));
    return p != 0;
}
__device__ __forceinline__ uint32_t gtime() {
    uint32_t t;
    asm volatile("mov.u32 %0, %globaltimer_lo;" : "=r"(t));
    return t;
}
__device__ __forceinline__ uint4 ld_poll4(const void* p) {
    uint64_t lo, hi;
    asm volatile("ld.relaxed.gpu.global.v2.b64 {%0,%1}, [%2];" : "=l"(lo), "=l"(hi) : "l"(p) : "memory");
    return make_uint4((uint32_t)lo, (uint32_t)(lo >> 32), (uint32_t)hi, (uint32_t)(hi >> 32));
}
__device__ __forceinline__ void ld_poll4_if(uint4& v, const void* p, uint32_t c) {
    uint64_t lo, hi;
    asm volatile("{\n.reg .pred q;\nsetp.ne.u32 q, %3, 0;\n@q ld.relaxed.gpu.global.v2.b64 {%0,%1}, [%2];\n}" : "=l"(lo), "=l"(hi) : "l"(p), "r"(c) : "memory");
    v = make_uint4((uint32_t)lo, (uint32_t)(lo >> 32), (uint32_t)hi, (uint32_t)(hi >> 32));
}
__device__ __forceinline__ void ld_poll4_keep(uint4& v, const void* p, uint32_t c) {
    asm volatile("{\n.reg .pred q;\nsetp.ne.u32 q, %5, 0;\n@q ld.relaxed.gpu.global.v4.u32 {%0,%1,%2,%3}, [%4];\n}"
                 : "+r"(v.x), "+r"(v.y), "+r"(v.z), "+r"(v.w) : "l"(p), "r"(c) : "memory");
}
__device__ __forceinline__ void ld_poll4_keep2(uint4& v, const void* p, uint32_t c) {
    uint64_t lo = (uint64_t)v.x | ((uint64_t)v.y << 32), hi = (uint64_t)v.z | ((uint64_t)v.w << 32);
    asm volatile("{\n.reg .pred q;\nsetp.ne.u32 q, %3, 0;\n@q ld.relaxed.gpu.global.v2.b64 {%0,%1}, [%2];\n}" : "+l"(lo), "+l"(hi) : "l"(p), "r"(c) : "memory");
    v = make_uint4((uint32_t)lo, (uint32_t)(lo >> 32), (uint32_t)hi, (uint32_t)(hi >> 32));
}
__device__ __forceinline__ void sts128_if(uint32_t a, uint32_t x, uint32_t y, uint32_t z, uint32_t w, uint32_t c) {
    asm volatile("{\n.reg .pred q;\nsetp.ne.u32 q, %5, 0;\n@q st.shared.v4.u32 [%0], {%1,%2,%3,%4};\n}" ::"r"(a), "r"(x), "r"(y), "r"(z), "r"(w), "r"(c) : "memory");
}
__device__ __forceinline__ uint32_t ne2(uint32_t a, uint32_t b, uint32_t c) {
    uint32_t d;
    asm("lop3.b32 %0, %1, %2, %3, 0x7E;" : "=r"(d) : "r"(a), "r"(b), "r"(c));
    return d;
}
__device__ __forceinline__ uint2 ld_poll2(const void* p) {
    uint64_t v;
    asm volatile("ld.relaxed.gpu.global.b64 %0, [%1];" : "=l"(v) : "l"(p) : "memory");
    return make_uint2((uint32_t)v, (uint32_t)(v >> 32));
}
__device__ __forceinline__ void st_pub2(void* p, uint32_t a, uint32_t b) {
    asm volatile("st.relaxed.gpu.global.b64 [%0], %1;" ::"l"(p), "l"((uint64_t)a | ((uint64_t)b << 32)) : "memory");
}
__device__ __forceinline__ uint32_t ld_poll(const void* p) {
    uint32_t v;
    asm volatile("ld.relaxed.gpu.global.u32 %0, [%1];" : "=r"(v) : "l"(p) : "memory");
    return v;
}
__device__ __forceinline__ void st_pub(void* p, uint32_t v) {
    asm volatile("st.relaxed.gpu.global.u32 [%0], %1;" ::"l"(p), "r"(v) : "memory");
}
__device__ __forceinline__ void st_pub4(void* p, uint32_t a, uint32_t b, uint32_t c, uint32_t d) {
    uint64_t lo = (uint64_t)a | ((uint64_t)b << 32), hi = (uint64_t)c | ((uint64_t)d << 32);
    asm volatile("st.relaxed.gpu.global.v2.b64 [%0], {%1, %2};" ::"l"(p), "l"(lo), "l"(hi) : "memory");
}
__device__ __forceinline__ void red_add(void* p, uint32_t v) {
    asm volatile("red.relaxed.gpu.global.add.u32 [%0], %1;" ::"l"(p), "r"(v) : "memory");
}
__device__ __forceinline__ uint32_t lds32(uint32_t a) {
    uint32_t v;
    asm volatile("ld.shared.u32 %0, [%1];" : "=r"(v) : "r"(a) : "memory");
    return v;
}
__device__ __forceinline__ uint32_t lds32v(uint32_t a) {
    uint32_t v;
    asm volatile("ld.volatile.shared.u32 %0, [%1];" : "=r"(v) : "r"(a) : "memory");
    return v;
}
__device__ __forceinline__ uint32_t lds16(uint32_t a) {
    uint32_t v;
    asm volatile("ld.shared.u16 %0, [%1];" : "=r"(v) : "r"(a) : "memory");
    return v;
}
__device__ __forceinline__ float ldsf(uint32_t a) { return __uint_as_float(lds32(a)); }
__device__ __forceinline__ float2 lds64f(uint32_t a) {
    float2 v;
    asm volatile("ld.shared.v2.f32 {%0,%1}, [%2];" : "=f"(v.x), "=f"(v.y) : "r"(a) : "memory");
    return v;
}
__device__ __forceinline__ void sts32(uint32_t a, uint32_t v) { asm volatile("st.shared.u32 [%0], %1;" ::"r"(a), "r"(v) : "memory"); }
__device__ __forceinline__ void stsf(uint32_t a, float v) { sts32(a, __float_as_uint(v)); }
__device__ __forceinline__ void sts16(uint32_t a, uint32_t v) { asm volatile("st.shared.u16 [%0], %1;" ::"r"(a), "h"((uint16_t)v) : "memory"); }
__device__ __forceinline__ void sts64(uint32_t a, uint32_t x, uint32_t y) {
    asm volatile("st.shared.v2.u32 [%0], {%1,%2};" ::"r"(a), "r"(x), "r"(y) : "memory");
}
__device__ __forceinline__ void sts64f(uint32_t a, float x, float y) { sts64(a, __float_as_uint(x), __float_as_uint(y)); }
__device__ __forceinline__ void bar_all() { asm volatile("bar.sync 1, 288;" ::: "memory"); }
__device__ __forceinline__ void bar_sync(int id, int n) { asm volatile("bar.sync %0, %1;" ::"r"(id), "r"(n) : "memory"); }
__device__ __forceinline__ void bar_arrive(int id, int n) { asm volatile("bar.arrive %0, %1;" ::"r"(id), "r"(n) : "memory"); }
__device__ __forceinline__ uint4 lds128(uint32_t a) {
    uint4 v;
    asm volatile("ld.shared.v4.u32 {%0,%1,%2,%3}, [%4];" : "=r"(v.x), "=r"(v.y), "=r"(v.z), "=r"(v.w) : "r"(a) : "memory");
    return v;
}
__device__ __forceinline__ float4 lds128f(uint32_t a) {
    float4 v;
    asm volatile("ld.shared.v4.f32 {%0,%1,%2,%3}, [%4];" : "=f"(v.x), "=f"(v.y), "=f"(v.z), "=f"(v.w) : "r"(a) : "memory");
    return v;
}
__device__ __forceinline__ void sts128(uint32_t a, uint32_t x, uint32_t y, uint32_t z, uint32_t w) {
    asm volatile("st.shared.v4.u32 [%0], {%1,%2,%3,%4};" ::"r"(a), "r"(x), "r"(y), "r"(z), "r"(w) : "memory");
}
__device__ __forceinline__ void sts128f(uint32_t a, float x, float y, float z, float w) {
    sts128(a, __float_as_uint(x), __float_as_uint(y), __float_as_uint(z), __float_as_uint(w));
}
__device__ __forceinline__ uint32_t hadd2(uint32_t a, uint32_t b) {
    __nv_bfloat162 s = __hadd2(*(__nv_bfloat162*)&a, *(__nv_bfloat162*)&b);
    return *(uint32_t*)&s;
}
__device__ __forceinline__ float shfl_xor_v(float v, int m) {
    float r;
    asm volatile("shfl.sync.bfly.b32 %0, %1, %2, 0x1f, 0xffffffff;" : "=f"(r) : "f"(v), "r"(m));
    return r;
}
#define SPIN_GUARD(n) do { if (++(n) > (1u << 20)) __trap(); } while (0)

__device__ __forceinline__ void mbar_wait4(uint32_t bar0, int lane) {
    mbar_wait(bar0 + 24);
    mbar_wait(bar0 + 8 * (lane & 3));
    __syncwarp();
}

__device__ __forceinline__ float reduce8(float (&s)[8], int lane) {
    const bool u4 = lane & 16, u3 = lane & 8, u2 = lane & 4;
#pragma unroll
    for (int i = 0; i < 4; i++) s[i] = (u4 ? s[i + 4] : s[i]) + shfl_xor_v(u4 ? s[i] : s[i + 4], 16);
#pragma unroll
    for (int i = 0; i < 2; i++) s[i] = (u3 ? s[i + 2] : s[i]) + shfl_xor_v(u3 ? s[i] : s[i + 2], 8);
    return (u2 ? s[1] : s[0]) + shfl_xor_v(u2 ? s[0] : s[1], 4);
}

__device__ __forceinline__ void load_wide_frags(uint32_t (&a)[4][4], uint32_t a0) {
#pragma unroll
    for (int mt = 0; mt < 4; mt++) ldsm4t(a[mt], a0 ^ (mt << 5));
}

__device__ __forceinline__ void send_partials(char* gb, const uint32_t (&po)[4], const float (&d)[4][4], int lane, uint32_t tag16) {
    const bool hi = lane & 2;
#pragma unroll
    for (int mt = 0; mt < 4; mt++) st_pub(gb + po[mt], pack2_tag(hi ? d[mt][2] : d[mt][0], hi ? d[mt][3] : d[mt][1], tag16));
}

__global__ void __launch_bounds__(NTHR, 1) __cluster_dims__(2, 1, 1)
fused_kernel(const __nv_bfloat16* __restrict__ x, const __nv_bfloat16* __restrict__ cvec, const __nv_bfloat16* __restrict__ w_mod,
             __nv_bfloat16* __restrict__ out, char* __restrict__ gb, const __grid_constant__ Maps maps) {
    extern __shared__ __align__(1024) unsigned char smem[];
    const uint32_t sb = (uint32_t)__cvta_generic_to_shared(smem);
    const int tid = threadIdx.x, w = __shfl_sync(~0u, tid >> 5, 0), lane = tid & 31;
    const int id = blockIdx.x, P = id >> 1, r = id & 1;
    const int h = (P >> 4) * 8 + (P & 7), p = (P >> 3) & 1;
    const bool heavy = id >= 96;
    const bool is_red = id < 72;
    const int j = id;
    const bool has_mod = id >= 24 && id < 96;
    const uint32_t gubox = heavy ? 6144u : 4096u;
    const uint32_t wdbase = heavy ? OFF_WQ - 18432 : OFF_WQ;
    const int g = lane >> 2, t = lane & 3;
    const int i4 = lane >> 3, rho = lane & 7;
    const int rep = P & 1;
    const uint32_t peer = r ^ 1;
    auto BAR = [&](int i) { return sb + OFF_BAR + 8u * i; };
    auto parity = [&]() { return lds32(sb + OFF_SIDE + 28) & 1u; };
    KS(0);

    uint64_t pol;
    asm volatile("createpolicy.fractional.L2::evict_first.b64 %0, 1.0;" : "=l"(pol));
    const uint32_t t0 = gtime();
    uint32_t ep_raw = 0;
    if (w == 15 || w < 2) ep_raw = ld_poll(gb + G_EPOCH);
    if (w >= 9 && w < 12 && lane < 27)
        asm volatile("prefetch.global.L2 [%0];" ::"l"((const char*)w_mod + (size_t)(P * 9 + (w - 9) * 3 + lane / 9) * 6912 + r * 1152 + (lane % 9) * 128) : "memory");
    if (w == 12) {
        if (elect()) {
            mbar_init(BAR(B_CX), 1);
#pragma unroll
            for (int i = 0; i < NFAST; i++) mbar_init(BAR(i), 1);
            mbar_arrive_tx(BAR(B_CX), 9216);
            bulk_g2s(sb + OFF_C, cvec, 4608, BAR(B_CX));
            bulk_g2s(sb + OFF_X, x, 4608, BAR(B_CX));
        }
        __syncwarp();
        bar_arrive(15, 320);
        bar_arrive(14, 192);
        if (elect()) {
#pragma unroll
            for (int i = 0; i < NFAST; i++) {
                mbar_arrive_tx(BAR(i), 9216);
                tma4d(sb + OFF_WQ + i * 9216, &maps.m[M_WQ], 128 * h + 64 * p, 0, 0, 288 * r + 72 * i, BAR(i), pol);
            }
        }
        TS(39);
    }
    __syncwarp();
    if (w == 15) {
        asm volatile("barrier.cluster.arrive.relaxed.aligned;" ::: "memory");
        const uint32_t off0 = G_PROBE + dup(id * 512), off1 = (1 + (id >> 5)) * PAGE + dup((id & 31) * 512);
        st_pub4(gb + off0 + lane * 16, 0, 0, 0, 0);
        st_pub4(gb + off0 + 4096 + lane * 16, 0, 0, 0, 0);
        st_pub4(gb + off1 + (lane >> 4) * 4096 + (lane & 15) * 16, 0, 0, 0, 0);
        const uint32_t ep = ep_raw + 1;
        sts32(sb + OFF_SIDE, 2u);
        sts32(sb + OFF_SIDE + 28, ep);
        bar_arrive(4, NTHR - 32);
        while (gtime() - t0 < (is_red ? TPROBE : TPROBE2));
        uint32_t dep = 0, s0 = 0, sd = 0;
#pragma unroll 1
        for (int rnd = 0; rnd < 2; rnd++) {
            const uint32_t off = rnd ? off1 : off0;
            int score = 0;
#pragma unroll 1
            for (int i = 0; i < 4 - 2 * rnd; i++) {
                const uint32_t c0 = clock_after(dep);
                dep = ld_poll(gb + off + i * 128 + dep);
                const uint32_t c1 = clock_after(dep);
                dep = ld_poll(gb + off + 4096 + i * 128 + dep);
                const int ta = (int)(c1 - c0), tb = (int)(clock_after(dep) - c1);
                const bool sure = min(ta, tb) < 350 && abs(ta - tb) > 130;
                score = (sure ? 0 : score) + max(-200, min(200, ta - tb));
                sd = __shfl_sync(~0u, (__popc(off & 0xB2000u) ^ (score > 0 ? 1u : 0u)) & 1u, 0);
                if (rnd == 0) { s0 = sd; asm volatile("st.volatile.shared.u32 [%0], %1;" ::"r"(sb + OFF_SIDE), "r"(sd) : "memory"); }
                if (sure) break;
            }
            if (rnd == 0) KS(42);
        }
        const uint32_t word = ep * 4 + (sd ^ s0) * 2 + s0;
        if (lane < 4) st_pub4(gb + G_TAB + (lane >> 1) * 4096 + id * 32 + (lane & 1) * 16, word, word, word, word);
        const char* tab = gb + sided(G_TAB, s0) + lane * 32;
        uint32_t r0, r1, r2, r3, n = 0;
        bar_sync(0, 192);
#pragma unroll 1
        while (!mbar_try(BAR(B_SX), 0)) SPIN_GUARD(n);
#pragma unroll 1
        do {
            SPIN_GUARD(n);
            r0 = ld_poll(tab);
            r1 = ld_poll(tab + 1024);
            r2 = ld_poll(tab + 2048);
            r3 = ld_poll(tab + 3072);
        } while (!__all_sync(~0u, (ne2(r0, r1, word) | ne2(r2, r3, word)) < 4u));
        auto vote = [&](uint32_t v) { return (uint32_t)(__popc(__ballot_sync(~0u, v & 2u)) > 16); };
        const uint32_t pf = vote(r0) | (vote(r1) << 1) | (vote(r2) << 2) | (vote(r3) << 3);
        const int src = 2 * lane + r;
        const uint32_t a0 = __shfl_sync(~0u, r0, src), a1 = __shfl_sync(~0u, r1, src), a2 = __shfl_sync(~0u, r2, src), a3 = __shfl_sync(~0u, r3, src);
        const uint32_t slo = __ballot_sync(~0u, (lane < 16 ? a0 : a1) & 1u), shi = __ballot_sync(~0u, (lane < 16 ? a2 : a3) & 1u);
        const int n0 = 64 - __popc(slo) - __popc(shi);
        const int c1 = __popcll((((uint64_t)shi << 32) | slo) & ((1ull << P) - 1)), pos = s0 ? n0 + c1 : P - c1;
        const uint32_t fa = __ballot_sync(~0u, ((lane + 32 * (int)s0 >= n0) ^ (pf >> i4) ^ __popc((G_INB + (rho * 2 + r) * 65536 + dup(P * 512)) & 0xB2000u)) & 1u);
        const uint32_t ps = G_PART + lane * 16384 + dup(id * 64);
        const uint32_t k0 = __ballot_sync(~0u, (r0 ^ __popc(ps & 0xB2000u)) & 1u), k1 = __ballot_sync(~0u, (r1 ^ __popc((ps + 32 * 16384) & 0xB2000u)) & 1u);
        const uint32_t k2 = __ballot_sync(~0u, (r2 ^ __popc((ps + 64 * 16384) & 0xB2000u)) & 1u);
        const uint32_t cpage = (1 + ((pos >> 3) & 3)) * PAGE, cib = (pos & 7) * 2 + r, cxo = cpage + G_CX + cib * 16384 + (pos >> 5) * 8192;
        const uint32_t csd = s0 ^ (pf >> ((pos >> 3) & 3));
        sts32(sb + OFF_SIDE + 4, fa);
        sts64(sb + OFF_SIDE + 8, pos < 32 ? ~slo : slo, pos < 32 ? ~shi : shi);
        sts128(sb + OFF_SIDE + 16, k0, k1, k2, ep);
        sts128(sb + OFF_SIDE + 48, sided(cpage + G_STAT + dup(cib * 2048), csd), sided(cpage + G_INB + cib * 65536, csd), cxo,
               sided((1 + (id >> 5)) * PAGE + G_CX + ((h & 7) * 2 + r) * 16384, s0 ^ (pf >> (id >> 5))));
        __syncwarp();
        if (lane == 0) mbar_arrive(BAR(B_TAB));
        KS(38);
        uint64_t rows = (((uint64_t)shi << 32) | slo) ^ (pos < 32 ? ~0ull : 0ull);
        const uint32_t rb = sided(cpage + G_INB + cib * 65536, csd) + lane * 16;
#pragma unroll 1
        for (int k = 0; k < 2; k++) {
#pragma unroll 1
            while (!mbar_try(BAR(k ? B_DONE : RSTBAR), 0))
                if (gtime() - t0 > 500000000u) __trap();
#pragma unroll 1
            for (; rows; rows &= rows - 1) {
                const uint32_t i = __ffsll(rows) - 1;
                st_pub4(gb + ((rb ^ ((i & 8) << 9)) + (i >> 3) * 8192 + (i & 7) * 512), 0u, 0u, 0u, 0u);
            }
            if (k == 0) KS(46);
        }
        return;
    }

    if (w == 12) {
        asm volatile("barrier.cluster.arrive.relaxed.aligned;" ::: "memory");
        const int f0 = heavy ? 48 * id - 1536 : 32 * id;
        const int nbox = heavy ? 47 : has_mod ? 49 : 45;
        auto box_of = [&](int e) { return has_mod || e < B_MOD ? e : e + 4; };
#pragma unroll 1
        for (int e0 = NFAST; e0 < nbox; e0 += 32) {
            const int e = e0 + lane, c = box_of(e);
            const int win = e < B_MOD ? WIN : !heavy ? WL : c < B_WD ? WH : WH + 2;
            const int ep = e - win;
            const uint32_t bar = BAR(c), pbar = BAR(box_of(ep));
            const int i = c & 3;
            int map = M_WQ, c0 = 128 * h + 64 * p, c2 = 0, c3 = 288 * r + 72 * i, dep = -1;
            uint32_t dst = OFF_WQ + i * 9216;
            if (c >= B_WUK) { map = M_WUK; c3 = 256 * r + 64 * i; dst = OFF_WUK + i * 8192; }
            if (c >= B_WUV) { map = M_WUV; dst = OFF_WUV + i * 8192; dep = i == 0 ? B_FREE_T1 : -1; }
            else if (c >= B_CKV) { map = M_CKV; c0 = 64 * (c & 1); c2 = 2 * r; c3 = 32 * P + 4 * ((c - B_CKV) >> 1); dst = OFF_CKV + (c - B_CKV) * 8192; }
            if (c >= B_WO) { map = M_WO; c0 = 0; c3 = (32 * (4 * h + 2 * p + r) + 8 * i) * 9; dst = OFF_WQ + i * 9216; dep = i == 0 ? B_FREE_T4 : i == 2 ? B_FREE_SL : -1; }
            if (c >= B_MOD) { map = M_MOD; c0 = 4192 - 32 * id; c3 = 144 * i; dst = OFF_MODR + i * 9216; dep = i != 0 ? -1 : B_FREE_T4; }
            if (c >= B_GU) {
                const int k = c - B_GU;
                map = heavy ? M_G48 : M_G32; c0 = f0; c3 = 64 * k; dst = OFF_RINGE - (2 * k + 2) * gubox;
                dep = k == 0 ? B_FREE_RING : has_mod && k == 7 ? B_FREE_MOD : heavy && k == 8 ? B_FREE_WUV : -1;
            }
            if (c >= B_WD) {
                const int k = c - B_WD;
                map = M_WD; c0 = 0; c3 = (f0 + 8 * k) * 9; dst = wdbase + k * 9216;
                dep = k == (heavy ? 2 : 0) ? B_FREE_WO : -1;
            }
            const uint32_t tfl = c < 4 ? TSTART + c * RAMP : c < B_MOD ? TSTART + 4 * RAMP + (c - 4) * DT8
                               : TTAIL0 + (e - B_MOD) * (heavy ? TTAIL / 15 : has_mod ? TTAIL / 17 : TTAIL / 13);
            const uint32_t mo = map * 128 + (map >= M_G32 && map < M_WD), db = dep >= 0 ? BAR(dep) : 0u, pb = ep >= 0 ? pbar : 0u;
            dst += sb;
            const int nn = min(32, nbox - e0);
            if (e0 == NFAST) bar_sync(9, 192);
#pragma unroll 1
            for (int n = 0; n < nn; n++) {
                const uint32_t u_db = __shfl_sync(~0u, db, n), u_pb = __shfl_sync(~0u, pb, n), u_tf = __shfl_sync(~0u, tfl, n);
                const uint32_t u_dst = __shfl_sync(~0u, dst, n), u_bar = __shfl_sync(~0u, bar, n), u_mo = __shfl_sync(~0u, mo, n);
                const int u_c0 = __shfl_sync(~0u, c0, n), u_c2 = __shfl_sync(~0u, c2, n), u_c3 = __shfl_sync(~0u, c3, n);
                const char* tm = (const char*)&maps + (u_mo & ~1u);
                if (u_db) mbar_wait(u_db);
                if (u_pb) mbar_wait(u_pb);
                while (gtime() - t0 < u_tf);
                if (elect()) {
                    tma4d(u_dst, tm, u_c0, 0, u_c2, u_c3, u_bar, pol);
                    if (u_mo & 1u) tma4d(u_dst + gubox, tm + 128, u_c0, 0, u_c2, u_c3, u_bar, pol);
                }
                TS(29 + (u_bar > BAR(2)) + (u_bar > BAR(23)) + (u_bar > BAR(31)) + (u_bar > BAR(44)));
            }
        }
        return;
    }
    if (w >= 9) {
        const int q = w - 9 - (w > 12);
        const int lo = NFAST + 18 * q, n = 18;
        if (lane == 0) {
            const uint32_t cnt = q < 3 ? 1u : 72u;
#pragma unroll
            for (int k = 0; k < 18; k++) mbar_init(BAR(lo) + 8 * k, cnt);
            asm volatile("fence.mbarrier_init.release.cluster;" ::: "memory");
        }
        __syncwarp();
        const int i = lo + lane;
        if (lane < n) {
            if (i < B_FREE_CW) mbar_arrive_tx(BAR(i), (i >= B_WUK && i < B_WO) ? 8192u : (i >= B_GU && i < B_WD) ? 2 * gubox : 9216u);
            if (i >= B_SX && i <= B_QP) mbar_expect_tx(BAR(i), i == B_QP ? 2048u : 4096u);
        }
        __syncwarp();
        bar_arrive(9, 192);
        bar_arrive(0, 192);
        bar_sync(14, 192);
        if (q < 4) {
            mbar_wait(BAR(B_CX));
            float mean = 0.f, acc = 0.f;
#pragma unroll 1
            for (int pass = 0; pass < 2; pass++) {
                mean = acc * (1.f / 576.f);
                acc = 0.f;
#pragma unroll
                for (int k = 0; k < 9; k++) {
                    const uint32_t v = lds32(sb + OFF_X + q * 1152 + k * 128 + lane * 4);
                    const float a = bf_lo(v) - mean, b = bf_hi(v) - mean;
                    acc += pass ? a * a + b * b : a + b;
                }
#pragma unroll
                for (int o = 16; o; o >>= 1) acc += shfl_xor_v(acc, o);
            }
            stsf(sb + OFF_LN1 + q * 4, mean);
            stsf(sb + OFF_LN1 + 16 + q * 4, rsqrtf(acc * (1.f / 576.f) + 1e-5f));
        }
        asm volatile("barrier.cluster.arrive.relaxed.aligned;" ::: "memory");
        if (w == 14 && lane == 0) prefetch_map(&maps.m[M_WUK]);
        __syncwarp();
        TSM(5);
        bar_sync(4, NTHR - 32);
        TSM(8);
        if (w == 13 && lane == 0) {
#pragma unroll 1
            for (int k = M_CKV; k < M_COUNT; k++) prefetch_map(&maps.m[k]);
        }
        __syncwarp();
        if (w == 14) {
            uint32_t cw[72];
#pragma unroll
            for (int s = 0; s < 18; s++) {
                const uint4 v = lds128(sb + OFF_MOD0 + (s >> 1) * 2048 + (s & 1) * 256 + (lane & 15) * 16);
                cw[4 * s] = v.x; cw[4 * s + 1] = v.y; cw[4 * s + 2] = v.z; cw[4 * s + 3] = v.w;
            }
            __syncwarp();
            if (lane == 0) mbar_arrive(BAR(B_FREE_CW));
            if (!has_mod) return;
            const uint32_t par = parity();
            const int sec = (95 - id) / 18;
            char* dst = gb + modv_off(t & 1, 2 + sec, 32 * (95 - id - 18 * sec) + 8 * (t >> 1) + g);
#pragma unroll
            for (int k = 0; k < 4; k++) st_pub2(dst + (k & 1) * 128 + (k >> 1) * 4096, par ^ 1u, 0u);
            float d[2][4];
#pragma unroll
            for (int a = 0; a < 2; a++) d[a][0] = d[a][1] = d[a][2] = d[a][3] = 0.f;
            const uint32_t mb = sb + OFF_MODR + ((i4 >> 1) * 8 + rho) * 64 + (((i4 & 1) ^ (rho >> 1)) << 4);
#pragma unroll
            for (int s = 0; s < 36; s++) {
                if (s % 9 == 0) mbar_wait(BAR(B_MOD + s / 9));
                uint32_t a0[4], a1[4];
                ldsm4t(a0, mb + s * 1024);
                ldsm4t(a1, (mb ^ 32) + s * 1024);
                mma(d[0], a0, cw[2 * s], cw[2 * s + 1]);
                mma(d[1], a1, cw[2 * s], cw[2 * s + 1]);
            }
            if (lane == 0) mbar_arrive(BAR(B_FREE_MOD));
#pragma unroll
            for (int mt = 0; mt < 2; mt++) {
                const float v0 = t < 2 ? d[mt][0] : d[mt][2], v1 = t < 2 ? d[mt][1] : d[mt][3];
                const uint32_t mine = (t & 1) ? pack2(v0, v1) : pack2_tag(v0, v1, par << 16);
                const uint32_t other = __shfl_xor_sync(~0u, mine, 1);
                const uint32_t lo_ = (t & 1) ? other : mine, hi_ = (t & 1) ? mine : other;
                st_pub2(dst + mt * 128, lo_, hi_);
                st_pub2(dst + mt * 128 + 4096, lo_, hi_);
            }
            KS(34);
            return;
        }
    } else {
        uint2 sav, cav;
        const uint32_t sao = modv_off(rep, 0, 288 * r + tid);
        if (is_red) {
            const char* wm = (const char*)w_mod + (size_t)(64 * w + (lane >> 1)) * 6912 + j * 32 + (lane & 1) * 16;
            const uint32_t d0 = sb + OFF_MOD0 + (64 * w + (lane >> 1)) * 32 + (((lane ^ (lane >> 3)) & 1) << 4);
#pragma unroll
            for (int q = 0; q < 4; q++)
                asm volatile("cp.async.cg.shared.global.L2::128B [%0], [%1], 16;" ::"r"(d0 + q * 512), "l"(wm + q * 16 * 6912) : "memory");
        }
        bar_sync(15, 320);
        mbar_wait(BAR(B_CX));
        uint32_t cz[4];
        ldsm4(cz, sb + OFF_C + (rho & 3) * 1152 + w * 128 + (rho >> 2) * 64 + i4 * 16);
#pragma unroll
        for (int s = 0; s < 4; s++) cz[s] = pack2(silu(bf_lo(cz[s])), silu(bf_hi(cz[s])));
        if (is_red) {
            char* const sdst = gb + modv_off(t >> 1, j >= 36, 16 * (j >= 36 ? j - 36 : j) + 8 * (w & 1) + g) + (t & 1) * 4096;
            if (w < 2) st_pub2(sdst, ep_raw & 1u, 0u);
            uint32_t co[4];
#pragma unroll
            for (int s = 0; s < 4; s++) co[s] = __shfl_xor_sync(~0u, cz[s], 16);
            const bool up = lane & 16;
            asm volatile("cp.async.wait_all;" ::: "memory");
            __syncwarp();
            TSM(1);
            float d[4] = {0.f, 0.f, 0.f, 0.f}, e[4] = {0.f, 0.f, 0.f, 0.f};
            uint32_t a[4][4];
#pragma unroll
            for (int s = 0; s < 4; s++)
                ldsm4t(a[s], sb + OFF_MOD0 + (64 * w + 16 * s + (i4 >> 1) * 8 + rho) * 32 + (((i4 ^ (rho >> 2)) & 1) << 4));
            mma(d, a[0], up ? co[0] : cz[0], up ? co[1] : cz[1]);
            mma(e, a[1], up ? co[2] : cz[2], up ? co[3] : cz[3]);
            mma(d, a[2], up ? cz[0] : co[0], up ? cz[1] : co[1]);
            mma(e, a[3], up ? cz[2] : co[2], up ? cz[3] : co[3]);
            sts64f(sb + OFF_RED + ((w * 16 + (t >> 1) * 8 + g) * 4 + (t & 1) * 2) * 4, t < 2 ? d[0] + e[0] : d[2] + e[2], t < 2 ? d[1] + e[1] : d[3] + e[3]);
            if (w >= 2) {
                bar_arrive(1, 288);
            } else {
                bar_all();
                float v[9];
#pragma unroll
                for (int i = 0; i < 9; i++) v[i] = ldsf(sb + OFF_RED + i * 256 + tid * 4);
                const float s0 = (((v[0] + v[1]) + (v[2] + v[3])) + ((v[4] + v[5]) + (v[6] + v[7]))) + v[8];
                const float b0 = __shfl_sync(~0u, s0, lane & 28), b1 = __shfl_sync(~0u, s0, (lane & 28) + 1);
                const float b2 = __shfl_sync(~0u, s0, (lane & 28) + 2), b3 = __shfl_sync(~0u, s0, (lane & 28) + 3);
                st_pub2(sdst, pack2_tag(b0, b1, ((ep_raw + 1) & 1u) << 16), pack2(b2, b3));
                KS(2);
            }
            if (w == 2) sts16(sb + OFF_XO + rho * 8 + i4 * 2, lds16(sb + OFF_X + i4 * 1152 + (8 * j + rho) * 2));
        }
        sts128(sb + OFF_MOD0 + w * 2048 + lane * 16, cz[0], cz[1], cz[2], cz[3]);
        uint32_t xc[4];
#pragma unroll
        for (int b = 0; b < 4; b++) xc[b] = lds16(sb + OFF_X + b * 1152 + (288 * r + tid) * 2);
        asm volatile("barrier.cluster.arrive.relaxed.aligned;" ::: "memory");
        bar_sync(4, NTHR - 32);
        TS0(3);
        const uint32_t par = parity();
        const uint32_t qdst = G_QABS + ((g & 3) * 2 + r) * 65536 + (g >> 2) * 4096 +
                              dup((p * 1024 + ((w >> 1) & 1) * 512 + ((w >> 2) * 32 + h) * 8 + (((w & 1) * 4 + t) ^ (h & 7))) * 16);
        if (w < 8) st_pub4(gb + qdst, par ^ 1u, 0u, par ^ 1u, 0u);

        const float4 mu = lds128f(sb + OFF_LN1), rs = lds128f(sb + OFF_LN1 + 16);
        asm volatile("barrier.cluster.wait.aligned;" ::: "memory");
        const int kh = (w >> 2) & 1, mt = w & 3;
        uint32_t a[9][4];
        mbar_wait(BAR(B_WQ + 2 * kh));
        mbar_wait(BAR(B_WQ + 2 * kh + 1));
#pragma unroll
        for (int s = 0; s < 9; s++) ldsm4t(a[s], sb + OFF_WQ + (144 * kh + 16 * s + (i4 >> 1) * 8 + rho) * 128 + (((2 * mt + (i4 & 1)) ^ rho) << 4));
        uint32_t side;
        while ((side = lds32v(sb + OFF_SIDE)) > 1u || gtime() - t0 < T1POLL);
        const char* sasrc = gb + sided(sao, side);
#pragma unroll 1
        do {
            sav = ld_poll2(sasrc);
            cav = ld_poll2(sasrc + 16384);
        } while (__any_sync(~0u, ne2(sav.x, cav.x, par) & 1u));
        const uint32_t ha = sb + OFF_HS + tid * 2;
        sts16(ha, pack2((bf_lo(xc[0]) - mu.x) * rs.x * (1.f + bf_lo(cav.x)) + bf_lo(sav.x), 0.f));
        sts16(ha + 1168, pack2((bf_lo(xc[1]) - mu.y) * rs.y * (1.f + bf_hi(cav.x)) + bf_hi(sav.x), 0.f));
        sts16(ha + 2336, pack2((bf_lo(xc[2]) - mu.z) * rs.z * (1.f + bf_lo(cav.y)) + bf_lo(sav.y), 0.f));
        sts16(ha + 3504, pack2((bf_lo(xc[3]) - mu.w) * rs.w * (1.f + bf_hi(cav.y)) + bf_hi(sav.y), 0.f));
        KS(4);
        bar_all();
        if (w < 8) {
            {
                const uint32_t hb = sb + OFF_HS + (rho & 3) * 1168 + 288 * kh + i4 * 16;
                uint32_t bh[5][4];
#pragma unroll
                for (int s = 0; s < 5; s++) ldsm4(bh[s], hb + s * 64);
                float d[3][4];
#pragma unroll
                for (int s = 0; s < 3; s++) d[s][0] = d[s][1] = d[s][2] = d[s][3] = 0.f;
#pragma unroll
                for (int s = 0; s < 9; s++) mma(d[s % 3], a[s], bh[s >> 1][(s & 1) * 2], bh[s >> 1][(s & 1) * 2 + 1]);
                const float v0 = t < 2 ? d[0][0] + d[1][0] + d[2][0] : d[0][2] + d[1][2] + d[2][2];
                const float v1 = t < 2 ? d[0][1] + d[1][1] + d[2][1] : d[0][3] + d[1][3] + d[2][3];
                const uint32_t qa = sb + OFF_SP + ((2 * r + kh) * 256 + (16 * mt + (t >> 1) * 8 + g) * 4 + (t & 1) * 2) * 4;
                st_async2(mapa(qa, peer), v0, v1, mapa(BAR(B_QP), peer));
                sts64f(qa, v0, v1);
                __syncwarp();
                if (lane == 0) mbar_arrive(BAR(B_QP), 9);
                TS0(6);
            }
            mbar_wait(BAR(B_QP));
            const uint32_t qa = sb + OFF_SP + tid * 4;
            sts16(sb + OFF_ACT + (tid & 3) * 144 + (tid >> 2) * 2, pack2((ldsf(qa) + ldsf(qa + 1024)) + (ldsf(qa + 2048) + ldsf(qa + 3072)), 0.f));
            bar_sync(2, 256);
            KS(7);
            uint32_t aq[2][4], bq[4][2][4];
            ldsm4(aq[0], sb + OFF_ACT + (rho & 3) * 144 + i4 * 16);
            ldsm4(aq[1], sb + OFF_ACT + (rho & 3) * 144 + i4 * 16 + 64);
            mbar_wait(BAR(B_WUK + (w >> 1)));
#pragma unroll
            for (int i = 0; i < 4; i++) {
                const int rl = 2 * ((i + (rho >> 1)) & 3) + (rho & 1);
                const uint32_t ua = sb + OFF_WUK + (32 * w + 8 * (rho >> 1) + rl) * 128 + ((i4 ^ rl) << 4);
                ldsm4(bq[i][0], ua);
                ldsm4(bq[i][1], ua ^ 64);
            }
            float d[4][4];
#pragma unroll
            for (int i = 0; i < 4; i++) d[i][0] = d[i][1] = d[i][2] = d[i][3] = 0.f;
#pragma unroll
            for (int s = 0; s < 4; s++)
#pragma unroll
                for (int i = 0; i < 4; i++)
                    mma(d[i], aq[s >> 1][(s & 1) * 2], 0u, aq[s >> 1][(s & 1) * 2 + 1], 0u, bq[i][s >> 1][(s & 1) * 2], bq[i][s >> 1][(s & 1) * 2 + 1]);
            const float sc = 0.08838834764831845f * 1.4426950408889634f;
            uint32_t u[4];
#pragma unroll
            for (int i = 0; i < 4; i++) {
                const float lo = d[i][0] * sc, hi = d[i][1] * sc;
                u[i] = ((i + t) & 1) ? pack2(lo, hi) : pack2_tag(lo, hi, par << 16);
            }
            if (t & 1) { const uint32_t z = u[3]; u[3] = u[2]; u[2] = u[1]; u[1] = u[0]; u[0] = z; }
            if (t & 2) { uint32_t z = u[0]; u[0] = u[2]; u[2] = z; z = u[1]; u[1] = u[3]; u[3] = z; }
            st_pub4(gb + qdst, u[0], u[1], u[2], u[3]);
            if (lane == 0) mbar_arrive_remote(mapa(BAR(B_PEER_WUK), peer), 9);
            KS(9);
        }
    }

    if (w < 12 && (w & 4) == 0) {
        const int k = (w >> 2) + ((w >> 1) & 1);
        const uint32_t blk = (k & 1) * 2 + (k >> 1), par = parity();
        const uint32_t qs = sb + OFF_MOD0 + blk * 4096 + (tid & 63) * 16;
        mbar_wait(BAR(B_FREE_CW));
        mbar_wait(BAR(B_QP));
        mbar_wait(BAR(B_WUK + k));
        const char* q0 = gb + sided(G_QABS + ((P >> 4) * 2 + r) * 65536 + blk * 8192, lds32v(sb + OFF_SIDE)) + (tid & 63) * 16;
        uint32_t pend = 15u, c0 = gtime() + QDELAY;
#pragma unroll 1
        do {
            while ((int)(gtime() - c0) < 0);
            c0 = gtime() + QPERIOD;
            uint4 u0[4], u1[4];
#pragma unroll
            for (int i = 0; i < 4; i++) {
                ld_poll4_if(u0[i], q0 + i * 1024, pend & (1u << i));
                ld_poll4_if(u1[i], q0 + 32768 + i * 1024, pend & (1u << i));
            }
            uint32_t bad = 0;
#pragma unroll
            for (int i = 0; i < 4; i++) {
                bad |= ((ne2(u0[i].x, u0[i].z, par) | ne2(u1[i].x, u1[i].z, par)) & 1u) << i;
                sts128_if(qs + i * 1024, hadd2(u0[i].x, u1[i].x), hadd2(u0[i].y, u1[i].y), hadd2(u0[i].z, u1[i].z), hadd2(u0[i].w, u1[i].w),
                          pend & (1u << i));
            }
            pend &= bad;
        } while (__any_sync(~0u, pend != 0));
        fence_async();
        KS(12);
        bar_arrive(3, 384);
    }
    const uint32_t sbu = __shfl_sync(~0u, sb & 0x3FFFFu, 0);
    if (w < 4) {
        float o[4][16];
#pragma unroll
        for (int m = 0; m < 4; m++)
#pragma unroll
            for (int i = 0; i < 16; i++) o[m][i] = 0.f;
        uint32_t eo[8];
        const uint32_t npar = parity() ^ 1u;
        char* const fdst = gb + stat_off(tid >> 2, r, P, t);
        st_pub4(fdst, npar, 0u, npar, 0u);
#pragma unroll 1
        for (int tile = 0; tile < 8; tile++) {
            if (tile == 5) {
                mbar_wait(BAR(B_TAB));
                const uint32_t fa = lds32(sb + OFF_SIDE + 4);
                const uint32_t rowo = G_INB + r * 65536 + dup(P * 512 + ((w * 8 + g) << 4));
#pragma unroll
                for (int v = 0; v < 8; v++) {
                    const int hl = 2 * (t ^ (v >> 1)) + (v & 1), hh = 8 * (v >> 1) + hl;
                    eo[v] = (1 + (v >> 1)) * PAGE + hl * 131072 + rowo + (((fa >> hh) & 1u) << 12);
                }
            }
            const uint32_t da = desc_lo(sbu + OFF_CKV + tile * 16384, 16);
            const uint32_t dp = desc_lo(sbu + OFF_SX + tile * 4096, 128);
            bar_sync(5 + tile + (tile > 4), 256);
            float2 al[4];
#pragma unroll
            for (int i = 0; i < 4; i++) al[i] = lds64f(sb + OFF_SX + tile * 4096 + i * 1024 + 512 + t * 32);
#pragma unroll
            for (int hm = 0; hm < 4; hm += 2) {
#pragma unroll
                for (int m = hm; m < hm + 2; m++) {
#pragma unroll
                    for (int i = 0; i < 16; i++) o[m][i] *= (i & 1) ? al[i >> 2].y : al[i >> 2].x;
                    pin(o[m]);
                }
                wg_fence();
#pragma unroll
                for (int ks = 0; ks < 2; ks++)
#pragma unroll
                    for (int m = hm; m < hm + 2; m++) wgmma_pv(o[m], da + (m & 1) * 512 + (m >> 1) * 64 + ks * 256, dp + ks * 16);
                wg_commit();
            }
            TS0(48 + (tile & 6));
            if (tile == 7) bar_sync(10, 256);
            wg_wait0();
#pragma unroll
            for (int m = 0; m < 4; m++) pin(o[m]);
            if (lane == 0 && (0x92 >> tile & 1)) mbar_arrive(BAR(B_FREE_T1 + tile / 3), 18);
        }
        KS(13);
        const float2 ml = lds64f(sb + OFF_RED + (tid >> 2) * 8);
#pragma unroll
        for (int v = 0; v < 8; v++) {
            const int e0 = (v >> 1) * 4 + (v & 1);
            const uint32_t u0 = pack2_tag(o[0][e0], o[0][e0 + 2], 0x10000u), u1 = pack2(o[1][e0], o[1][e0 + 2]);
            const uint32_t u2 = pack2_tag(o[2][e0], o[2][e0 + 2], 0x10000u), u3 = pack2(o[3][e0], o[3][e0 + 2]);
            st_pub4(gb + eo[v], u0, u1, u2, u3);
        }
        st_pub4(fdst, __float_as_uint(ml.x), __float_as_uint(ml.y), __float_as_uint(ml.x), __float_as_uint(ml.y));
        KS(14);
    } else if (w < 8) {
        const int wl = w & 3;
        const uint32_t dq = desc_lo(sbu + OFF_MOD0, 16);
        const uint32_t xo_ = (wl * 8 + g) * 128 + ((t ^ wl) << 5) + ((g & 1) << 4);
        mbar_wait(BAR(B_PEER_WUK));
        bar_sync(3, 384);
#pragma unroll 1
        for (int tile = 0; tile < 8; tile++) {
            const uint32_t da = desc_lo(sbu + OFF_CKV + tile * 16384, 16);
            float s[32];
            mbar_wait(BAR(B_CKV + 2 * tile));
            wg_fence();
            wgmma_s<0>(s, da, dq);
#pragma unroll
            for (int kk = 1; kk < 4; kk++) wgmma_s<1>(s, da + kk * 2, dq + kk * 2);
            mbar_wait(BAR(B_CKV + 2 * tile + 1));
            wg_fence();
#pragma unroll
            for (int kk = 0; kk < 4; kk++) wgmma_s<1>(s, da + 512 + kk * 2, dq + 512 + kk * 2);
            wg_commit();
            KS(44);
            const uint32_t sxr = mapa(sb + OFF_SX + tile * 4096 + xo_, peer), sbr = mapa(BAR(B_SX + tile), peer);
            const uint32_t sl = sb + (tile < 6 ? OFF_WQ : OFF_SL - 24576) + tile * 4096 + xo_;
            wg_wait0();
            pin(s);
            float y[8];
#pragma unroll
            for (int i = 0; i < 4; i++) {
                const float lo = s[(i >> 1) * 4 + (i & 1)] + s[16 + (i >> 1) * 4 + 2 + (i & 1)];
                const float hi = s[8 + (i >> 1) * 4 + (i & 1)] + s[24 + (i >> 1) * 4 + 2 + (i & 1)];
                y[i] = (g & 1) ? hi : lo;
                y[4 + i] = (g & 1) ? lo : hi;
            }
            st_async4(sxr, y[0], y[1], y[2], y[3], sbr);
            st_async4(sxr ^ 16, y[4], y[5], y[6], y[7], sbr);
            sts128f(sl, y[0], y[1], y[2], y[3]);
            sts128f(sl ^ 16, y[4], y[5], y[6], y[7]);
            __syncwarp();
            if (lane == 0) mbar_arrive(BAR(B_SX + tile), 18);
        }
    } else if (w < 12) {
        const int wl = w & 3;
        const uint32_t par = parity();
        const uint32_t ro = ((rho & 3) * 8 + i4) * 128 + ((wl ^ (rho & 3)) << 5) + (rho >> 2) * 16;
        const int ng = (g >> 2) * 2 + (t >> 1);
        const uint32_t po = ng * 1024 + ((wl ^ ng) << 5);
        float mrun = -INFINITY, lrun = 0.f;
#pragma unroll 1
        for (int tile = 0; tile < 8; tile++) {
            const uint32_t sx = sb + OFF_SX + tile * 4096, sl = sb + (tile < 6 ? OFF_WQ : OFF_SL - 24576) + tile * 4096 + ro;
            mbar_wait(BAR(B_SX + tile));
            uint32_t ua[2][4], ub[2][4];
            ldsm4(ua[0], sx + ro);
            ldsm4(ub[0], sl);
            ldsm4(ua[1], sx + ro + 512);
            ldsm4(ub[1], sl + 512);
            float v[8];
#pragma unroll
            for (int i = 0; i < 8; i++) v[i] = __uint_as_float(ua[i >> 2][i & 3]) + __uint_as_float(ub[i >> 2][i & 3]);
            const float mx = fmaxf(fmaxf(fmaxf(v[0], v[1]), fmaxf(v[2], v[3])), fmaxf(fmaxf(v[4], v[5]), fmaxf(v[6], v[7])));
            const float mn = fmaxf(fmaxf(fmaxf(mx, mrun), shfl_xor_v(mx, 4)), fmaxf(shfl_xor_v(mx, 8), shfl_xor_v(mx, 12)));
            const float al = ex2(mrun - mn);
            mrun = mn;
#pragma unroll
            for (int i = 0; i < 8; i++) v[i] = ex2(v[i] - mn);
            sts128(sx + po + (g & 3) * 128 + (t & 1) * 16, pack2(v[0], v[1]), pack2(v[2], v[3]), pack2(v[4], v[5]), pack2(v[6], v[7]));
            stsf(sx + po + 512 + (t & 1) * 4, al);
            fence_async();
            bar_arrive(5 + tile + (tile > 4), 256);
            if (lane == 0 && tile == 5) mbar_arrive(BAR(B_FREE_SL), 18);
            lrun = lrun * al + (((v[0] + v[1]) + (v[2] + v[3])) + ((v[4] + v[5]) + (v[6] + v[7])));
        }
        if (lane == 0) mbar_arrive_remote(mapa(BAR(B_PEER_SL), peer), 18);
        lrun += shfl_xor_v(lrun, 4);
        lrun += shfl_xor_v(lrun, 8);
        sts64(sb + OFF_RED + (8 * ng + 2 * wl + (t & 1)) * 8, (__float_as_uint(mrun) & ~1u) | par, __float_as_uint(lrun));
        bar_arrive(10, 256);
    }

    mbar_wait(BAR(B_TAB));
    const uint32_t par = parity(), side = lds32(sb + OFF_SIDE);
    uint32_t po[4];
    if (w < 9) {
        const uint32_t km = lds32(sb + OFF_SIDE + 16 + (w >> 2) * 4) >> ((w & 3) * 8 + (t >> 1));
#pragma unroll
        for (int mt = 0; mt < 4; mt++) po[mt] = G_PART + (8 * w + 2 * mt + (t >> 1)) * 16384 + dup(id * 64) + (((km >> (2 * mt)) & 1u) << 12) + g * 8 + (t & 1) * 4;
    }
    if (w == 13) {
        char* pz = gb + G_PART + g * 16384 + dup(id * 64) + t * 16;
#pragma unroll 1
        for (int i = 0; i < 9; i++) st_pub4(pz + i * 131072 + (((lds32(sb + OFF_SIDE + 16 + (i >> 2) * 4) >> ((i & 3) * 8 + g)) & 1u) << 12), 0u, 0u, 0u, 0u);
        const uint32_t z = par ^ 1u;
        char* cz_ = gb + lds32(sb + OFF_SIDE + 56) + (lane >> 4) * 4096 + (lane & 15) * 16;
#pragma unroll 1
        for (int i = 0; i < 10; i++) st_pub4(cz_ + i * 256, z, z, z, z);
        __syncwarp();
        if (lane == 0) mbar_arrive(BAR(B_CLR));
    }
    if (w >= 4 && w < 12) {
        const int b = (w - 4) >> 1, hi = lane >> 4, ch = (w & 1) * 16 + (lane & 15);
        char* const cxd = gb + lds32(sb + OFF_SIDE + 56) + hi * 4096 + (b * 32 + ch) * 4;
        const uint32_t rows = (lds32(sb + OFF_SIDE + 8 + (b >> 1) * 4) >> ((b & 1) * 16)) & 0xFFFFu;
        const char* fsrc = gb + lds32(sb + OFF_SIDE + 48) + (b * 16 + (lane & 15)) * 32;
        const bool here = (rows >> (lane & 15)) & 1u;
        const uint32_t ro = lds32(sb + OFF_SIDE + 52) + b * 16384 + hi * 512 + ch * 16;
        const char* r0 = gb + ro;
        const char* r1 = gb + (ro ^ 12288u);
        uint4 v[8];
#pragma unroll
        for (int i = 0; i < 8; i++) v[i] = make_uint4(0u, 0u, 0u, 0u);
        mbar_wait(BAR(B_CLR));
        mbar_wait(BAR(B_FREE_RING));
        uint2 f;
        uint32_t seen = 0;
#pragma unroll 1
        do {
            f = ld_poll2(fsrc);
            const uint32_t go = __ballot_sync(~0u, ((f.x ^ par) & 1u) == 0) & rows & ~seen;
            seen |= go;
#pragma unroll
            for (int i = 0; i < 8; i++) ld_poll4_keep2(v[i], (i < 4 ? r0 : r1) + (i & 3) * 1024, (go >> hi) & (1u << (2 * i)));
        } while (seen != rows);
        const float m = here ? __uint_as_float(f.x) : -1.7e38f;
        float M = m;
#pragma unroll
        for (int o = 1; o < 16; o <<= 1) M = fmaxf(M, shfl_xor_v(M, o));
        const float wt = ex2(m - M);
        float L = here ? wt * __uint_as_float(f.y) : 0.f;
#pragma unroll
        for (int o = 1; o < 16; o <<= 1) L += shfl_xor_v(L, o);
        const float wn = L > 0.f ? wt * rcp(L) : 0.f;
        float wr[8];
#pragma unroll
        for (int i = 0; i < 8; i++) wr[i] = __shfl_sync(~0u, wn, 2 * i + hi);
#pragma unroll 1
        while (true) {
            uint32_t ok = 0;
#pragma unroll
            for (int i = 0; i < 8; i++) ok |= (v[i].x & v[i].z & 1u) << (2 * i);
            const uint32_t pend = (rows >> hi) & 0x5555u & ~ok;
            if (!__any_sync(~0u, pend != 0)) break;
#pragma unroll
            for (int i = 0; i < 8; i++) ld_poll4_keep2(v[i], (i < 4 ? r0 : r1) + (i & 3) * 1024, pend & (1u << (2 * i)));
        }
        KS(16);
        float acc[8];
#pragma unroll
        for (int e = 0; e < 8; e++) acc[e] = 0.f;
#pragma unroll
        for (int i = 0; i < 8; i++) {
            acc[0] += wr[i] * bf_lo(v[i].x); acc[1] += wr[i] * bf_hi(v[i].x); acc[2] += wr[i] * bf_lo(v[i].y); acc[3] += wr[i] * bf_hi(v[i].y);
            acc[4] += wr[i] * bf_lo(v[i].z); acc[5] += wr[i] * bf_hi(v[i].z); acc[6] += wr[i] * bf_lo(v[i].w); acc[7] += wr[i] * bf_hi(v[i].w);
        }
#pragma unroll
        for (int e = 0; e < 8; e++) acc[e] += shfl_xor_v(acc[e], 16);
        st_pub4(cxd + (b * 32 + ch) * 12, pack2_tag(acc[0], acc[1], par << 16), pack2(acc[2], acc[3]), pack2_tag(acc[4], acc[5], par << 16), pack2(acc[6], acc[7]));
        st_pub(cxd + 2048, (__float_as_uint(fmaxf(M + __log2f(L), -3e38f)) & ~1u) | par);
        if (lane == 0) mbar_arrive(BAR(B_FREE_INB3), 9);
        KS(17);
    }

    if (w >= 9) {
        if (!is_red) return;
        const int q = w - 9 - (w > 12);
        const char* src = gb + sided(G_PART + j * 16384 + (q >> 1) * 8192, side) + (q & 1) * 2048 + (2 * t + (g >> 2)) * 64 + (g & 3) * 16;
        const uint32_t sel = (g & 1) ? 0x3F800000u : 0x00003F80u;
        char* const xdst = gb + modv_off(lane >> 4, 6, 8 * j + rho) + (i4 & 1) * 4096;
        if (q == 0) st_pub2(xdst, par ^ 1u, 0u);
        const float2 xo = lds64f(sb + OFF_XO + rho * 8);
        float y0 = bf_lo(__float_as_uint(xo.x)), y1 = bf_hi(__float_as_uint(xo.x)), y2 = bf_lo(__float_as_uint(xo.y)), y3 = bf_hi(__float_as_uint(xo.y));
#pragma unroll 1
        for (int it = 1; it >= 0; it--) {
            const char* gsrc = gb + sided(modv_off(rep, it ? 2 : 5, 8 * j + rho), side);
            uint2 gv;
            uint4 v[4];
            uint32_t n = 0, pend = 15u;
            if (q == 0) {
#pragma unroll 1
                do gv = ld_poll2(gsrc);
                while (__any_sync(~0u, (gv.x ^ par) & 1u));
            }
            bar_sync(14, 160);
#pragma unroll 1
            do {
                SPIN_GUARD(n);
#pragma unroll
                for (int i = 0; i < 4; i++) ld_poll4_keep(v[i], src + i * 512, pend & (1u << i));
                pend = 0;
#pragma unroll
                for (int i = 0; i < 4; i++) pend |= ((ne2(v[i].x, v[i].y, it) | ne2(v[i].z, v[i].w, it)) & 1u) << i;
            } while (__any_sync(~0u, pend != 0));
            KS(it ? 20 : 27);
            float e[4][4];
#pragma unroll
            for (int k = 0; k < 4; k++) {
                const uint32_t ak = (g >> 1) == k ? sel : 0u;
                e[k][0] = e[k][1] = e[k][2] = e[k][3] = 0.f;
                mma(e[k], ak, 0u, ak, 0u, k == 0 ? v[0].x : k == 1 ? v[0].y : k == 2 ? v[0].z : v[0].w, k == 0 ? v[1].x : k == 1 ? v[1].y : k == 2 ? v[1].z : v[1].w);
                mma(e[k], ak, 0u, ak, 0u, k == 0 ? v[2].x : k == 1 ? v[2].y : k == 2 ? v[2].z : v[2].w, k == 0 ? v[3].x : k == 1 ? v[3].y : k == 2 ? v[3].z : v[3].w);
            }
            const uint32_t za = sb + OFF_RED + 256 + (q * 2 + (t >> 1)) * 128 + (t & 1) * 64 + g * 4;
            stsf(za, (e[0][0] + e[1][0]) + (e[2][0] + e[3][0]));
            stsf(za + 32, (e[0][1] + e[1][1]) + (e[2][1] + e[3][1]));
            if (q != 0) {
                bar_arrive(2, 128);
            } else {
                bar_sync(2, 128);
                const uint32_t ra = sb + OFF_RED + 256 + rho * 16;
                float4 z[8];
#pragma unroll
                for (int i = 0; i < 8; i++) z[i] = lds128f(ra + i * 128);
                const float4 a = make_float4(z[0].x + z[1].x, z[0].y + z[1].y, z[0].z + z[1].z, z[0].w + z[1].w);
                const float4 b = make_float4(z[2].x + z[3].x, z[2].y + z[3].y, z[2].z + z[3].z, z[2].w + z[3].w);
                const float4 c = make_float4(z[4].x + z[5].x, z[4].y + z[5].y, z[4].z + z[5].z, z[4].w + z[5].w);
                const float4 d = make_float4(z[6].x + z[7].x, z[6].y + z[7].y, z[6].z + z[7].z, z[6].w + z[7].w);
                y0 += bf_lo(gv.x) * ((a.x + b.x) + (c.x + d.x));
                y1 += bf_hi(gv.x) * ((a.y + b.y) + (c.y + d.y));
                y2 += bf_lo(gv.y) * ((a.z + b.z) + (c.z + d.z));
                y3 += bf_hi(gv.y) * ((a.w + b.w) + (c.w + d.w));
                if (it) {
                    st_pub2(xdst, pack2_tag(y0, y1, par << 16), pack2(y2, y3));
                } else {
                    out[i4 * 576 + 8 * j + rho] = __float2bfloat16(i4 == 0 ? y0 : i4 == 1 ? y1 : i4 == 2 ? y2 : y3);
                    if (id == 0 && lane == 0) red_add(gb + G_EPOCH, 1);
                }
                KS(it ? 21 : 28);
            }
        }
        return;
    }

    const uint32_t wseg = ((i4 >> 1) * 8 + rho) * 9 + w, wfo = wseg * 128 + (((i4 & 1) ^ (wseg & 7)) << 4);
    const uint32_t acta = sb + OFF_ACT + (rho & 3) * 144 + i4 * 16;
    if (w < 8) {
        uint32_t av[2][4][4];
        mbar_wait4(BAR(B_WUV), lane);
#pragma unroll
        for (int s = 0; s < 2; s++) {
            const int rl = 4 * (w & 1) + (rho >> 1);
            load_wide_frags(av[s], sb + OFF_WUV + (64 * (2 * s + (i4 >> 1)) + 16 * (w >> 1) + 8 * (rho & 1) + rl) * 128 + (((i4 & 1) ^ rl) << 4));
        }
        __syncwarp();
        if (lane == 0) mbar_arrive(BAR(B_FREE_WUV), 9);
        mbar_wait(BAR(B_FREE_INB3));
        mbar_wait(BAR(B_PEER_SL));
        TS0(35);
        uint32_t u[4];
        {
            const uint32_t o0 = lds32(sb + OFF_SIDE + 60);
            const int pc = (g & 3) * 32 + 4 * w + t, cxs = 2048 - pc * 12;
            const char* c0 = gb + o0 + pc * 16;
            const char* c1 = gb + (o0 ^ 12288u) + pc * 16;
            uint4 a, b;
            uint32_t la, lb;
#pragma unroll 1
            do {
                a = ld_poll4(c0); b = ld_poll4(c1);
                la = ld_poll(c0 + cxs); lb = ld_poll(c1 + cxs);
            } while (__any_sync(~0u, (ne2(a.x, a.z, par) | ne2(b.x, b.z, par) | ne2(la, lb, par)) & 1u));
            KS(15);
            const float dl = __uint_as_float(lb) - __uint_as_float(la);
            const float fa_ = rcp(1.f + ex2(dl)), fb_ = rcp(1.f + ex2(-dl));
            u[0] = pack2(fa_ * bf_lo(a.x) + fb_ * bf_lo(b.x), fa_ * bf_hi(a.x) + fb_ * bf_hi(b.x));
            u[1] = pack2(fa_ * bf_lo(a.y) + fb_ * bf_lo(b.y), fa_ * bf_hi(a.y) + fb_ * bf_hi(b.y));
            u[2] = pack2(fa_ * bf_lo(a.z) + fb_ * bf_lo(b.z), fa_ * bf_hi(a.z) + fb_ * bf_hi(b.z));
            u[3] = pack2(fa_ * bf_lo(a.w) + fb_ * bf_lo(b.w), fa_ * bf_hi(a.w) + fb_ * bf_hi(b.w));
        }
        float d[4][4];
#pragma unroll
        for (int mt = 0; mt < 4; mt++) {
            d[mt][0] = d[mt][1] = d[mt][2] = d[mt][3] = 0.f;
            mma(d[mt], av[0][mt], u[0], u[1]);
        }
#pragma unroll
        for (int mt = 0; mt < 4; mt++) mma(d[mt], av[1][mt], u[2], u[3]);
        const uint32_t ca = sb + OFF_CP + (r * 8 + w) * 512 + (((t >> 1) * 8 + g) * 4 + (t & 1) * 2) * 4;
        const uint32_t cr = mapa(ca, peer), cbar = mapa(BAR(B_CP), peer);
#pragma unroll
        for (int m2 = 0; m2 < 2; m2++) {
            const float a0 = t < 2 ? d[m2][0] : d[m2][2], a1 = t < 2 ? d[m2][1] : d[m2][3];
            const float b0 = t < 2 ? d[2 + m2][0] : d[2 + m2][2], b1 = t < 2 ? d[2 + m2][1] : d[2 + m2][3];
            st_async2(cr + m2 * 256, r ? a0 : b0, r ? a1 : b1, cbar);
            sts64f(ca + m2 * 256, r ? b0 : a0, r ? b1 : a1);
        }
        __syncwarp();
        if (lane == 0) mbar_arrive(BAR(B_CP), 9);
    }

    {
        uint32_t a[2][4][4];
        mbar_wait4(BAR(B_WO), lane);
        load_wide_frags(a[0], sb + OFF_WQ + wfo);
        load_wide_frags(a[1], sb + OFF_WQ + 18432 + wfo);
        __syncwarp();
        if (lane == 0) mbar_arrive(BAR(B_FREE_WO), 8);
        TS0(36);
        if (w < 4) {
            mbar_wait(BAR(B_CP));
            TS0(18);
            float v[16];
#pragma unroll
            for (int i = 0; i < 16; i++) v[i] = ldsf(sb + OFF_CP + i * 512 + tid * 4);
            const float cs = (((v[0] + v[1]) + (v[2] + v[3])) + ((v[4] + v[5]) + (v[6] + v[7]))) +
                             (((v[8] + v[9]) + (v[10] + v[11])) + ((v[12] + v[13]) + (v[14] + v[15])));
            sts16(sb + OFF_ACT + (tid & 3) * 144 + (tid >> 2) * 2, pack2(cs, 0.f));
        }
        bar_all();
        uint32_t b[4];
        ldsm4(b, acta);
        float d[4][4];
#pragma unroll
        for (int mt = 0; mt < 4; mt++) {
            d[mt][0] = d[mt][1] = d[mt][2] = d[mt][3] = 0.f;
            mma(d[mt], a[0][mt], b[0], b[1]);
        }
#pragma unroll
        for (int mt = 0; mt < 4; mt++) mma(d[mt], a[1][mt], b[2], b[3]);
        send_partials(gb, po, d, lane, 0x10000u);
        if (w == 8 && is_red) bar_arrive(14, 160);
        KS(19);
    }

    {
        const uint32_t pitch = heavy ? 96u : 64u;
        const uint32_t gua = sb + OFF_RINGE - (w + 1) * 2 * gubox + ((i4 >> 1) * 8 + rho) * pitch + (((i4 & 1) ^ (heavy ? 0 : rho >> 1)) << 4);
        const uint32_t gub = heavy ? gua + 32 : gua ^ 32;
        const uint32_t co = sided(modv_off(rep, 4, 2 * tid), side);
        const char* msrc = gb + ((co ^ 4096u) - 16384);
        const char* csrc = gb + co;
        const char* xsrc = csrc + 32768;
        uint4 sbv, cbv;
#pragma unroll 1
        do {
            sbv = ld_poll4(msrc);
            cbv = ld_poll4(csrc);
        } while (__any_sync(~0u, (ne2(sbv.x, sbv.z, par) | ne2(cbv.x, cbv.z, par)) & 1u));
        uint32_t ag[2][4][4], au[2][4][4], hb[2][4];
        bool have_w = false, have_h = false;
#pragma unroll 1
        do {
            uint4 xv;
            if (!have_h) xv = ld_poll4(xsrc);
            if (!have_w && (have_h ? mbar_try(BAR(B_GU + w), 0) : mbar_test(BAR(B_GU + w), 0))) {
                have_w = true;
#pragma unroll
                for (int s2 = 0; s2 < 4; s2++) {
                    ldsm4t(ag[0][s2], gua + s2 * 16 * pitch);
                    ldsm4t(au[0][s2], gua + s2 * 16 * pitch + gubox);
                    ldsm4t(ag[1][s2], gub + s2 * 16 * pitch);
                    ldsm4t(au[1][s2], gub + s2 * 16 * pitch + gubox);
                }
            }
            if (!have_h && !__any_sync(~0u, ne2(xv.x, xv.z, par) & 1u)) {
                have_h = true;
                KS(22);
                const float4 pv = lds128f(sb + OFF_LN1);
                const float v[8] = {bf_lo(xv.x) - pv.x, bf_hi(xv.x) - pv.y, bf_lo(xv.y) - pv.z, bf_hi(xv.y) - pv.w,
                                    bf_lo(xv.z) - pv.x, bf_hi(xv.z) - pv.y, bf_lo(xv.w) - pv.z, bf_hi(xv.w) - pv.w};
                float s[8];
#pragma unroll
                for (int b = 0; b < 4; b++) { s[b] = v[b] + v[4 + b]; s[4 + b] = v[b] * v[b] + v[4 + b] * v[4 + b]; }
                stsf(sb + OFF_CP + w * 128 + lane * 4, reduce8(s, lane));
                bar_all();
                float tot;
                {
                    const uint32_t za = sb + OFF_CP + rho * 16 + i4 * 256;
                    const float4 z0 = lds128f(za), z1 = lds128f(za + 128);
                    tot = (((z0.x + z0.y) + (z0.z + z0.w)) + ((z1.x + z1.y) + (z1.z + z1.w))) + ldsf(sb + OFF_CP + 1024 + rho * 16 + i4 * 4);
                    tot = ((tot + shfl_xor_v(tot, 8)) + (shfl_xor_v(tot, 16) + shfl_xor_v(tot, 24))) * (1.f / 576.f);
                }
                const float oth = shfl_xor_v(tot, 4);
                const float mine = (lane & 4) ? rsqrtf(fmaxf(tot - oth * oth, 0.f) + 1e-5f) : tot;
                const uint32_t sw[4] = {sbv.x, sbv.y, sbv.z, sbv.w}, cwd[4] = {cbv.x, cbv.y, cbv.z, cbv.w};
#pragma unroll
                for (int b = 0; b < 4; b++) {
                    const float mean = __shfl_sync(~0u, mine, b), rstd = __shfl_sync(~0u, mine, 4 + b);
                    const float c0 = (b & 1) ? bf_hi(cwd[b >> 1]) : bf_lo(cwd[b >> 1]), c1 = (b & 1) ? bf_hi(cwd[2 + (b >> 1)]) : bf_lo(cwd[2 + (b >> 1)]);
                    const float s0 = (b & 1) ? bf_hi(sw[b >> 1]) : bf_lo(sw[b >> 1]), s1 = (b & 1) ? bf_hi(sw[2 + (b >> 1)]) : bf_lo(sw[2 + (b >> 1)]);
                    sts32(sb + OFF_HS + b * 1168 + tid * 4, pack2((v[b] - mean) * rstd * (1.f + c0) + s0, (v[4 + b] - mean) * rstd * (1.f + c1) + s1));
                }
                __syncwarp();
                ldsm4(hb[0], sb + OFF_HS + (rho & 3) * 1168 + w * 128 + i4 * 16);
                ldsm4(hb[1], sb + OFF_HS + (rho & 3) * 1168 + w * 128 + i4 * 16 + 64);
                KS(23);
            }
        } while (!(have_w && have_h));
        const uint32_t ra = sb + OFF_MOD0 + w * 1536 + (((t >> 1) * 8 + g) * 4 + (t & 1) * 2) * 4;
#pragma unroll 1
        for (int pass = 0;; pass++) {
            float dg[2][4], du[2][4];
#pragma unroll
            for (int mt = 0; mt < 2; mt++) { dg[mt][0] = dg[mt][1] = dg[mt][2] = dg[mt][3] = 0.f; du[mt][0] = du[mt][1] = du[mt][2] = du[mt][3] = 0.f; }
#pragma unroll
            for (int s2 = 0; s2 < 4; s2++)
#pragma unroll
                for (int mt = 0; mt < 2; mt++) {
                    mma(dg[mt], ag[mt][s2], hb[s2 >> 1][(s2 & 1) * 2], hb[s2 >> 1][(s2 & 1) * 2 + 1]);
                    mma(du[mt], au[mt][s2], hb[s2 >> 1][(s2 & 1) * 2], hb[s2 >> 1][(s2 & 1) * 2 + 1]);
                }
            const bool more = heavy && pass == 0;
            if (more) {
#pragma unroll
                for (int s2 = 0; s2 < 4; s2++) {
                    ldsm4t(ag[0][s2], gua + 64 + s2 * 1536);
                    ldsm4t(au[0][s2], gua + 64 + s2 * 1536 + 6144);
                }
            }
            sts64f(ra + pass * 512, t < 2 ? dg[0][0] : dg[0][2], t < 2 ? dg[0][1] : dg[0][3]);
            sts64f(ra + pass * 512 + 768, t < 2 ? du[0][0] : du[0][2], t < 2 ? du[0][1] : du[0][3]);
            sts64f(ra + 256, t < 2 ? dg[1][0] : dg[1][2], t < 2 ? dg[1][1] : dg[1][3]);
            sts64f(ra + 256 + 768, t < 2 ? du[1][0] : du[1][2], t < 2 ? du[1][1] : du[1][3]);
            if (!more) break;
        }
        bar_all();
        TS0(24);
        if (w < (heavy ? 6 : 4)) {
            float gz[9], uz[9];
#pragma unroll
            for (int i = 0; i < 9; i++) {
                gz[i] = ldsf(sb + OFF_MOD0 + i * 1536 + tid * 4);
                uz[i] = ldsf(sb + OFF_MOD0 + i * 1536 + 768 + tid * 4);
            }
            const float gsum = (((gz[0] + gz[1]) + (gz[2] + gz[3])) + ((gz[4] + gz[5]) + (gz[6] + gz[7]))) + gz[8];
            const float usum = (((uz[0] + uz[1]) + (uz[2] + uz[3])) + ((uz[4] + uz[5]) + (uz[6] + uz[7]))) + uz[8];
            sts16(sb + OFF_ACT + (tid & 3) * 144 + (tid >> 2) * 2, pack2(silu(gsum) * usum, 0.f));
        }
        uint32_t a[2][4][4], b[2][4];
        const uint32_t wda = sb + wdbase + wfo;
        mbar_wait(BAR(B_WD + 1));
        mbar_wait(BAR(B_WD));
        load_wide_frags(a[0], wda);
        if (heavy) {
            mbar_wait(BAR(B_WD + 3));
            mbar_wait(BAR(B_WD + 2));
            load_wide_frags(a[1], wda + 18432);
        }
        bar_all();
        KS(25);
        ldsm4(b[0], acta);
        ldsm4(b[1], acta + 64);
        float d[4][4];
#pragma unroll
        for (int mt = 0; mt < 4; mt++) {
            d[mt][0] = d[mt][1] = d[mt][2] = d[mt][3] = 0.f;
            mma(d[mt], a[0][mt], b[0][0], b[0][1]);
        }
        mbar_wait(BAR(B_WD + (heavy ? 4 : 2)));
        mbar_wait(BAR(B_WD + (heavy ? 5 : 3)));
        KS(43);
        load_wide_frags(a[0], wda + (heavy ? 36864 : 18432));
        if (heavy) {
#pragma unroll
            for (int mt = 0; mt < 4; mt++) mma(d[mt], a[1][mt], b[0][2], b[0][3]);
        }
#pragma unroll
        for (int mt = 0; mt < 4; mt++) mma(d[mt], a[0][mt], heavy ? b[1][0] : b[0][2], heavy ? b[1][1] : b[0][3]);
        send_partials(gb, po, d, lane, 0u);
        if (w == 8) {
            if (is_red) bar_arrive(14, 160);
            if (lane == 0) mbar_arrive(BAR(B_DONE));
        }
        KS(26);
    }
}

typedef CUresult (*EncodeFn)(CUtensorMap*, CUtensorMapDataType, cuuint32_t, void*, const cuuint64_t*, const cuuint64_t*,
                             const cuuint32_t*, const cuuint32_t*, CUtensorMapInterleave, CUtensorMapSwizzle,
                             CUtensorMapL2promotion, CUtensorMapFloatOOBfill);

void make_map(EncodeFn enc, CUtensorMap* m, const void* base, const cuuint64_t* dims, const cuuint64_t* strides,
              const cuuint32_t* box, CUtensorMapSwizzle swz) {
    cuuint32_t es[4] = {1, 1, 1, 1};
    enc(m, CU_TENSOR_MAP_DATA_TYPE_BFLOAT16, 4, const_cast<void*>(base), dims, strides, box, es,
        CU_TENSOR_MAP_INTERLEAVE_NONE, swz, CU_TENSOR_MAP_L2_PROMOTION_L2_128B, CU_TENSOR_MAP_FLOAT_OOB_FILL_NONE);
}

void make_map2(EncodeFn enc, CUtensorMap* m, const void* base, uint64_t cols, uint64_t rows, uint32_t bc, uint32_t br,
               CUtensorMapSwizzle swz) {
    cuuint64_t dims[4] = {cols, 1, 1, rows}, strides[3] = {cols * 2, cols * 2, cols * 2};
    cuuint32_t box[4] = {bc, 1, 1, br};
    make_map(enc, m, base, dims, strides, box, swz);
}

}

extern "C" void kernel_launch(void* const* d_in, const int* in_sizes, int n_in, void* d_out, int out_size) {
    (void)in_sizes; (void)n_in; (void)out_size;
    EncodeFn enc = nullptr;
    cudaDriverEntryPointQueryResult qr;
    cudaGetDriverEntryPoint("cuTensorMapEncodeTiled", (void**)&enc, cudaEnableDefault, &qr);
    Maps m;
    make_map2(enc, &m.m[M_WQ], d_in[2], 4096, 576, 64, 72, CU_TENSOR_MAP_SWIZZLE_128B);
    make_map2(enc, &m.m[M_WUK], d_in[3], 4096, 512, 64, 64, CU_TENSOR_MAP_SWIZZLE_128B);
    make_map2(enc, &m.m[M_WUV], d_in[4], 4096, 512, 64, 64, CU_TENSOR_MAP_SWIZZLE_128B);
    {
        cuuint64_t dims[4] = {128, 8, 4, 2048}, strides[3] = {1024, 256, 8192};
        cuuint32_t box[4] = {64, 8, 2, 4};
        make_map(enc, &m.m[M_CKV], d_in[1], dims, strides, box, CU_TENSOR_MAP_SWIZZLE_128B);
    }
    make_map2(enc, &m.m[M_WO], d_in[5], 64, 4096 * 9, 64, 72, CU_TENSOR_MAP_SWIZZLE_128B);
    make_map2(enc, &m.m[M_WD], d_in[9], 64, 4608 * 9, 64, 72, CU_TENSOR_MAP_SWIZZLE_128B);
    make_map2(enc, &m.m[M_MOD], d_in[11], 3456, 576, 32, 144, CU_TENSOR_MAP_SWIZZLE_64B);
    make_map2(enc, &m.m[M_G32], d_in[7], 4608, 576, 32, 64, CU_TENSOR_MAP_SWIZZLE_64B);
    make_map2(enc, &m.m[M_G32 + 1], d_in[8], 4608, 576, 32, 64, CU_TENSOR_MAP_SWIZZLE_64B);
    make_map2(enc, &m.m[M_G48], d_in[7], 4608, 576, 48, 64, CU_TENSOR_MAP_SWIZZLE_NONE);
    make_map2(enc, &m.m[M_G48 + 1], d_in[8], 4608, 576, 48, 64, CU_TENSOR_MAP_SWIZZLE_NONE);
    cudaFuncSetAttribute(fused_kernel, cudaFuncAttributeMaxDynamicSharedMemorySize, (int)SMEM_BYTES);
    void* gs = nullptr;
    cudaGetSymbolAddress(&gs, g_scratch);
    char* gb = (char*)(((uintptr_t)gs + PAGE - 1) & ~(uintptr_t)(PAGE - 1));
    fused_kernel<<<NCTA, NTHR, SMEM_BYTES>>>((const __nv_bfloat16*)d_in[0], (const __nv_bfloat16*)d_in[10],
                                            (const __nv_bfloat16*)d_in[11], (__nv_bfloat16*)d_out, gb, m);
}
```
